```python
import torch

def _softmax(x, axis=-1):
    return torch.softmax(x, dim=axis)
def _gelu(x):
    return torch.nn.functional.gelu(x, approximate="tanh")
def _silu(x):
    return torch.nn.functional.silu(x)
def _sigmoid(x):
    return torch.sigmoid(x)
def _layernorm(x, axis=-1, eps=1e-5):
    m = x.mean(dim=axis, keepdim=True)
    v = x.var(dim=axis, keepdim=True, unbiased=False)
    return (x - m) / torch.sqrt(v + eps)
def _scatter_add(tgt, idx, src, axis=0):
    return tgt.clone().index_add_(axis, idx, src)
def _segment_sum(src, seg, n):
    out = torch.zeros((n,) + src.shape[1:], dtype=src.dtype)
    return out.index_add_(0, seg, src)
def _pad(x, pw):
    flat = tuple(v for pair in reversed(pw) for v in pair)
    return torch.nn.functional.pad(x, flat)

kernel_name = 'interleave_layers__mha_block__grouped_kv_mqa__prompt'

def setup_inputs():

    _w = (lambda a: (lambda t: t.to(torch.bfloat16) if t.is_floating_point() else t)(torch.as_tensor(a)))
    def _A_setup():
        B, S, D, H = 1, 2048, 512, 32
        return {
            "x": _w((lambda *s: torch.randn(*s, dtype=torch.bfloat16) * 0.05)(B, S, D)),
            "wqkv": _w((lambda *s: torch.randn(*s, dtype=torch.bfloat16) * 0.05)(D, 3 * D)),
            "wo": _w((lambda *s: torch.randn(*s, dtype=torch.bfloat16) * 0.05)(D, D)),
        }
    _A_in = _A_setup()

    def _B_setup():
        B, S, D, H = 1, 2048, 512, 32
        Dh = D // H
        return {
            "x": _w((lambda *s: torch.randn(*s, dtype=torch.bfloat16) * 0.05)(B, S, D)),
            "wq": _w((lambda *s: torch.randn(*s, dtype=torch.bfloat16) * 0.1)(D, H * Dh)),
            "wk": _w((lambda *s: torch.randn(*s, dtype=torch.bfloat16) * 0.1)(D, Dh)),
            "wv": _w((lambda *s: torch.randn(*s, dtype=torch.bfloat16) * 0.05)(D, Dh)),
            "wo": _w((lambda *s: torch.randn(*s, dtype=torch.bfloat16) * 0.05)(H * Dh, D)),
        }
    _B_in = _B_setup()

    return {
        "A_x": _A_in["x"],
        "A_wqkv": _A_in["wqkv"],
        "A_wo": _A_in["wo"],
        "B_x": _B_in["x"],
        "B_wq": _B_in["wq"],
        "B_wk": _B_in["wk"],
        "B_wv": _B_in["wv"],
        "B_wo": _B_in["wo"],
    }

def reference(A_x, A_wqkv, A_wo, B_x, B_wq, B_wk, B_wv, B_wo):
    def _A_ref(x, wqkv, wo):
        B, S, D = x.shape
        H = 32
        Dh = D // H
        qkv = (lambda x, *d: x.permute(*d))((x @ wqkv).reshape(B, S, 3, H, Dh), 2, 0, 3, 1, 4)
        q, k, v = qkv[0], qkv[1], qkv[2]
        scores = torch.einsum("bhqd,bhkd->bhqk", q, k) * (Dh ** -0.5)
        p = _softmax(scores, axis=-1)
        o = torch.einsum("bhqk,bhkd->bhqd", p, v)
        return (lambda x, *d: x.permute(*d))(o, 0, 2, 1, 3).reshape(B, S, D) @ wo

    def _B_ref(x, wq, wk, wv, wo):
        B, S, D = x.shape
        H = 32
        Dh = D // H
        q = (lambda x, *d: x.permute(*d))((x @ wq).reshape(B, S, H, Dh), 0, 2, 1, 3)
        k = x @ wk
        v = x @ wv
        scores = torch.einsum("bhqd,bkd->bhqk", q, k) * (Dh ** -0.5)
        p = _softmax(scores, axis=-1)
        o = torch.einsum("bhqk,bkd->bhqd", p, v)
        return (lambda x, *d: x.permute(*d))(o, 0, 2, 1, 3).reshape(B, S, H * Dh) @ wo

    x = A_x
    x = x + _A_ref(_layernorm(x, axis=-1), A_wqkv, A_wo)
    x = x + _B_ref(_layernorm(x, axis=-1), B_wq, B_wk, B_wv, B_wo)
    x = x + _A_ref(_layernorm(x, axis=-1), A_wqkv, A_wo)
    x = x + _B_ref(_layernorm(x, axis=-1), B_wq, B_wk, B_wv, B_wo)
    return x
```

```cpp
#include <cuda_runtime.h>
#include <cuda_bf16.h>
#include <cuda_fp16.h>
#include <cuda.h>
#include <stdint.h>

namespace {

constexpr int S_ = 2048, D_ = 512, H_ = 32;

__device__ __align__(1024) __nv_bfloat16 g_x[S_ * D_];
__device__ __align__(1024) __nv_bfloat16 g_o[S_ * D_];
__device__ __align__(1024) uint4 g_q[H_ * S_ * 2];
__device__ __align__(1024) uint4 g_k[H_ * S_ * 2];
__device__ __align__(1024) uint4 g_v[H_ * S_ * 2];
__device__ __align__(16) float2 g_stats[S_ * 8];
__device__ __align__(16) float g_colsum[1536 + 512 + 32];
__device__ unsigned g_nrm[4 * 160];

__device__ __forceinline__ uint32_t s2u(const void* p) { return (uint32_t)__cvta_generic_to_shared(p); }
__device__ __forceinline__ void mbar_init(uint32_t bar, int cnt) {
  asm volatile("mbarrier.init.shared::cta.b64 [%0], %1;" ::"r"(bar), "r"(cnt) : "memory");
}
__device__ __forceinline__ void mbar_expect(uint32_t bar, uint32_t bytes) {
  asm volatile("mbarrier.arrive.expect_tx.shared::cta.b64 _, [%0], %1;" ::"r"(bar), "r"(bytes) : "memory");
}
__device__ __forceinline__ void mbar_arrive(uint32_t bar) {
  asm volatile("mbarrier.arrive.shared::cta.b64 _, [%0];" ::"r"(bar) : "memory");
}
__device__ __forceinline__ void mbar_wait(uint32_t bar, uint32_t par) {
  uint32_t ok;
  int it = 0;
  do {
    asm volatile("{.reg .pred p; mbarrier.try_wait.parity.shared::cta.b64 p, [%1], %2; selp.u32 %0,1,0,p;}"
                 : "=r"(ok) : "r"(bar), "r"(par) : "memory");
    if (++it > (1 << 24)) __trap();
  } while (!ok);
}
__device__ __forceinline__ void bulk_load(uint32_t dst, const void* src, uint32_t bytes, uint32_t bar) {
  asm volatile("cp.async.bulk.shared::cluster.global.mbarrier::complete_tx::bytes [%0], [%1], %2, [%3];"
               ::"r"(dst), "l"(src), "r"(bytes), "r"(bar) : "memory");
}
__device__ __forceinline__ void tma_load(uint32_t dst, const CUtensorMap* m, int c0, int c1, uint32_t bar) {
  asm volatile("cp.async.bulk.tensor.2d.shared::cluster.global.mbarrier::complete_tx::bytes [%0], [%1, {%3, %4}], [%2];"
               ::"r"(dst), "l"(m), "r"(bar), "r"(c0), "r"(c1) : "memory");
}
__device__ __forceinline__ void tma_prefetch_desc(const CUtensorMap* m) {
  asm volatile("prefetch.tensormap [%0];" ::"l"(m) : "memory");
}
__device__ __forceinline__ void pdl_wait() { asm volatile("griddepcontrol.wait;" ::: "memory"); }
__device__ __forceinline__ void pdl_launch() { asm volatile("griddepcontrol.launch_dependents;" ::: "memory"); }
__device__ __forceinline__ void fence_async_smem() { asm volatile("fence.proxy.async.shared::cta;" ::: "memory"); }
__device__ __forceinline__ void fence_bar_init() { asm volatile("fence.mbarrier_init.release.cluster;" ::: "memory"); }
__device__ __forceinline__ void named_sync(int id, int n) { asm volatile("bar.sync %0, %1;" ::"r"(id), "r"(n) : "memory"); }
__device__ __forceinline__ void wg_fence() { asm volatile("wgmma.fence.sync.aligned;" ::: "memory"); }
__device__ __forceinline__ void wg_commit() { asm volatile("wgmma.commit_group.sync.aligned;" ::: "memory"); }
template <int N> __device__ __forceinline__ void wg_wait() { asm volatile("wgmma.wait_group.sync.aligned %0;" ::"n"(N) : "memory"); }
template <int N> __device__ __forceinline__ void pin(float (&d)[N]) {
#pragma unroll
  for (int i = 0; i < N; i++) asm volatile("" : "+f"(d[i])::"memory");
}
template <int N> __device__ __forceinline__ void pin(uint32_t (&d)[N]) {
#pragma unroll
  for (int i = 0; i < N; i++) asm volatile("" : "+r"(d[i])::"memory");
}
__device__ __forceinline__ uint64_t mkdesc(uint32_t addr, uint32_t lbo, uint32_t sbo, uint64_t swz) {
  return (uint64_t)((addr & 0x3FFFF) >> 4) | ((uint64_t)(lbo >> 4) << 16) | ((uint64_t)(sbo >> 4) << 32) | (swz << 62);
}
__device__ __forceinline__ uint32_t pack_bf16(float lo, float hi) {
  uint32_t d; asm("cvt.rn.bf16x2.f32 %0, %1, %2;" : "=r"(d) : "f"(hi), "f"(lo)); return d;
}
__device__ __forceinline__ uint32_t pack_f16(float lo, float hi) {
  uint32_t d; asm("cvt.rn.f16x2.f32 %0, %1, %2;" : "=r"(d) : "f"(hi), "f"(lo)); return d;
}
__device__ __forceinline__ float bf_lo(uint32_t v) { return __uint_as_float(v << 16); }
__device__ __forceinline__ float bf_hi(uint32_t v) { return __uint_as_float(v & 0xffff0000u); }
__device__ __forceinline__ void stsm4(uint32_t addr, uint32_t a, uint32_t b, uint32_t c, uint32_t d) {
  asm volatile("stmatrix.sync.aligned.m8n8.x4.shared.b16 [%0], {%1,%2,%3,%4};" ::"r"(addr), "r"(a), "r"(b), "r"(c), "r"(d) : "memory");
}
__device__ __forceinline__ uint4 lds128(uint32_t addr) {
  uint4 v; asm volatile("ld.shared.v4.u32 {%0,%1,%2,%3}, [%4];" : "=r"(v.x), "=r"(v.y), "=r"(v.z), "=r"(v.w) : "r"(addr) : "memory"); return v;
}

__device__ __forceinline__ void wgmma_qk_n64(float (&d)[32], uint64_t da, uint64_t db) {
  asm volatile("wgmma.mma_async.sync.aligned.m64n64k16.f32.f16.f16 "
      "{%0,%1,%2,%3,%4,%5,%6,%7,%8,%9,%10,%11,%12,%13,%14,%15,%16,%17,%18,%19,%20,%21,%22,%23,%24,%25,%26,%27,%28,%29,%30,%31}, "
      "%32, %33, 1, 1, 1, 0, 0;"
    : "+f"(d[0]), "+f"(d[1]), "+f"(d[2]), "+f"(d[3]), "+f"(d[4]), "+f"(d[5]), "+f"(d[6]), "+f"(d[7]), "+f"(d[8]),
      "+f"(d[9]), "+f"(d[10]), "+f"(d[11]), "+f"(d[12]), "+f"(d[13]), "+f"(d[14]), "+f"(d[15]), "+f"(d[16]),
      "+f"(d[17]), "+f"(d[18]), "+f"(d[19]), "+f"(d[20]), "+f"(d[21]), "+f"(d[22]), "+f"(d[23]), "+f"(d[24]),
      "+f"(d[25]), "+f"(d[26]), "+f"(d[27]), "+f"(d[28]), "+f"(d[29]), "+f"(d[30]), "+f"(d[31])
    : "l"(da), "l"(db));
}
__device__ __forceinline__ void wgmma_pv_n24(float (&d)[12], uint32_t a0, uint32_t a1, uint32_t a2, uint32_t a3, uint64_t db) {
  asm volatile("wgmma.mma_async.sync.aligned.m64n24k16.f32.bf16.bf16 "
      "{%0,%1,%2,%3,%4,%5,%6,%7,%8,%9,%10,%11}, "
      "{%12,%13,%14,%15}, %16, 1, 1, 1, 1;"
    : "+f"(d[0]), "+f"(d[1]), "+f"(d[2]), "+f"(d[3]), "+f"(d[4]), "+f"(d[5]), "+f"(d[6]), "+f"(d[7]), "+f"(d[8]),
      "+f"(d[9]), "+f"(d[10]), "+f"(d[11])
    : "r"(a0), "r"(a1), "r"(a2), "r"(a3), "l"(db));
}
__device__ __forceinline__ void wgmma_gemm_n64(float (&d)[32], uint64_t da, uint64_t db) {
  asm volatile("wgmma.mma_async.sync.aligned.m64n64k16.f32.bf16.bf16 "
      "{%0,%1,%2,%3,%4,%5,%6,%7,%8,%9,%10,%11,%12,%13,%14,%15,%16,%17,%18,%19,%20,%21,%22,%23,%24,%25,%26,%27,%28,%29,%30,%31}, "
      "%32, %33, 1, 1, 1, 0, 1;"
    : "+f"(d[0]), "+f"(d[1]), "+f"(d[2]), "+f"(d[3]), "+f"(d[4]), "+f"(d[5]), "+f"(d[6]), "+f"(d[7]), "+f"(d[8]),
      "+f"(d[9]), "+f"(d[10]), "+f"(d[11]), "+f"(d[12]), "+f"(d[13]), "+f"(d[14]), "+f"(d[15]), "+f"(d[16]),
      "+f"(d[17]), "+f"(d[18]), "+f"(d[19]), "+f"(d[20]), "+f"(d[21]), "+f"(d[22]), "+f"(d[23]), "+f"(d[24]),
      "+f"(d[25]), "+f"(d[26]), "+f"(d[27]), "+f"(d[28]), "+f"(d[29]), "+f"(d[30]), "+f"(d[31])
    : "l"(da), "l"(db));
}
__device__ __forceinline__ void wgmma_gemm_n80(float (&d)[40], uint64_t da, uint64_t db) {
  asm volatile("wgmma.mma_async.sync.aligned.m64n80k16.f32.bf16.bf16 "
      "{%0,%1,%2,%3,%4,%5,%6,%7,%8,%9,%10,%11,%12,%13,%14,%15,%16,%17,%18,%19,%20,%21,%22,%23,%24,%25,%26,%27,%28,%29,%30,%31,%32,%33,%34,%35,%36,%37,%38,%39}, "
      "%40, %41, 1, 1, 1, 0, 1;"
    : "+f"(d[0]), "+f"(d[1]), "+f"(d[2]), "+f"(d[3]), "+f"(d[4]), "+f"(d[5]), "+f"(d[6]), "+f"(d[7]), "+f"(d[8]),
      "+f"(d[9]), "+f"(d[10]), "+f"(d[11]), "+f"(d[12]), "+f"(d[13]), "+f"(d[14]), "+f"(d[15]), "+f"(d[16]),
      "+f"(d[17]), "+f"(d[18]), "+f"(d[19]), "+f"(d[20]), "+f"(d[21]), "+f"(d[22]), "+f"(d[23]), "+f"(d[24]),
      "+f"(d[25]), "+f"(d[26]), "+f"(d[27]), "+f"(d[28]), "+f"(d[29]), "+f"(d[30]), "+f"(d[31]), "+f"(d[32]),
      "+f"(d[33]), "+f"(d[34]), "+f"(d[35]), "+f"(d[36]), "+f"(d[37]), "+f"(d[38]), "+f"(d[39])
    : "l"(da), "l"(db));
}
__device__ __forceinline__ void wgmma_gemm_n192(float (&d)[96], uint64_t da, uint64_t db) {
  asm volatile("wgmma.mma_async.sync.aligned.m64n192k16.f32.bf16.bf16 "
      "{%0,%1,%2,%3,%4,%5,%6,%7,%8,%9,%10,%11,%12,%13,%14,%15,%16,%17,%18,%19,%20,%21,%22,%23,%24,%25,%26,%27,%28,%29,%30,%31,%32,%33,%34,%35,%36,%37,%38,%39,%40,%41,%42,%43,%44,%45,%46,%47,%48,%49,%50,%51,%52,%53,%54,%55,%56,%57,%58,%59,%60,%61,%62,%63,%64,%65,%66,%67,%68,%69,%70,%71,%72,%73,%74,%75,%76,%77,%78,%79,%80,%81,%82,%83,%84,%85,%86,%87,%88,%89,%90,%91,%92,%93,%94,%95}, "
      "%96, %97, 1, 1, 1, 0, 1;"
    : "+f"(d[0]), "+f"(d[1]), "+f"(d[2]), "+f"(d[3]), "+f"(d[4]), "+f"(d[5]), "+f"(d[6]), "+f"(d[7]), "+f"(d[8]),
      "+f"(d[9]), "+f"(d[10]), "+f"(d[11]), "+f"(d[12]), "+f"(d[13]), "+f"(d[14]), "+f"(d[15]), "+f"(d[16]),
      "+f"(d[17]), "+f"(d[18]), "+f"(d[19]), "+f"(d[20]), "+f"(d[21]), "+f"(d[22]), "+f"(d[23]), "+f"(d[24]),
      "+f"(d[25]), "+f"(d[26]), "+f"(d[27]), "+f"(d[28]), "+f"(d[29]), "+f"(d[30]), "+f"(d[31]), "+f"(d[32]),
      "+f"(d[33]), "+f"(d[34]), "+f"(d[35]), "+f"(d[36]), "+f"(d[37]), "+f"(d[38]), "+f"(d[39]), "+f"(d[40]),
      "+f"(d[41]), "+f"(d[42]), "+f"(d[43]), "+f"(d[44]), "+f"(d[45]), "+f"(d[46]), "+f"(d[47]), "+f"(d[48]),
      "+f"(d[49]), "+f"(d[50]), "+f"(d[51]), "+f"(d[52]), "+f"(d[53]), "+f"(d[54]), "+f"(d[55]), "+f"(d[56]),
      "+f"(d[57]), "+f"(d[58]), "+f"(d[59]), "+f"(d[60]), "+f"(d[61]), "+f"(d[62]), "+f"(d[63]), "+f"(d[64]),
      "+f"(d[65]), "+f"(d[66]), "+f"(d[67]), "+f"(d[68]), "+f"(d[69]), "+f"(d[70]), "+f"(d[71]), "+f"(d[72]),
      "+f"(d[73]), "+f"(d[74]), "+f"(d[75]), "+f"(d[76]), "+f"(d[77]), "+f"(d[78]), "+f"(d[79]), "+f"(d[80]),
      "+f"(d[81]), "+f"(d[82]), "+f"(d[83]), "+f"(d[84]), "+f"(d[85]), "+f"(d[86]), "+f"(d[87]), "+f"(d[88]),
      "+f"(d[89]), "+f"(d[90]), "+f"(d[91]), "+f"(d[92]), "+f"(d[93]), "+f"(d[94]), "+f"(d[95])
    : "l"(da), "l"(db));
}


constexpr float QSCALE = 0.25f * 1.4426950408889634f;
constexpr float LN_EPS = 1e-5f;

__device__ __forceinline__ void row_stats(int row, float& mu, float& rstd) {
  const float4* p = reinterpret_cast<const float4*>(g_stats + row * 8);
  float4 a = __ldcg(p), b = __ldcg(p + 1), c = __ldcg(p + 2), d = __ldcg(p + 3);
  float s = (a.x + a.z) + (b.x + b.z) + (c.x + c.z) + (d.x + d.z);
  float q = (a.y + a.w) + (b.y + b.w) + (c.y + c.w) + (d.y + d.w);
  mu = s * (1.f / D_);
  float var = fmaxf(q * (1.f / D_) - mu * mu, 0.f);
  rstd = rsqrtf(var + LN_EPS);
}

__global__ void __launch_bounds__(256) prep_kernel(const __nv_bfloat16* __restrict__ x, const __nv_bfloat16* __restrict__ wqkv,
                                                   const __nv_bfloat16* __restrict__ wq, const __nv_bfloat16* __restrict__ wk,
                                                   const __nv_bfloat16* __restrict__ wv) {
  pdl_launch();
  __shared__ float red[8][16];
  const int b = blockIdx.x, tid = threadIdx.x, lane = tid & 31, warp = tid >> 5;
  if (b == 129) for (int i = tid; i < 4 * 160; i += 256) g_nrm[i] = 0u;
  {
    const __nv_bfloat16* w; int ld, out;
    if (b < 96) { w = wqkv + b * 16; ld = 1536; out = b * 16; }
    else if (b < 128) { w = wq + (b - 96) * 16; ld = 512; out = 1536 + (b - 96) * 16; }
    else { w = (b == 128) ? wk : wv; ld = 16; out = 2048 + (b - 128) * 16; }
    const int half = tid & 1, r0 = tid >> 1;
    float acc[8];
#pragma unroll
    for (int i = 0; i < 8; i++) acc[i] = 0.f;
#pragma unroll
    for (int j = 0; j < 4; j++) {
      uint4 v = __ldg(reinterpret_cast<const uint4*>(w + (size_t)(r0 + 128 * j) * ld + half * 8));
      acc[0] += bf_lo(v.x); acc[1] += bf_hi(v.x); acc[2] += bf_lo(v.y); acc[3] += bf_hi(v.y);
      acc[4] += bf_lo(v.z); acc[5] += bf_hi(v.z); acc[6] += bf_lo(v.w); acc[7] += bf_hi(v.w);
    }
#pragma unroll
    for (int i = 0; i < 8; i++) {
#pragma unroll
      for (int o = 2; o < 32; o <<= 1) acc[i] += __shfl_xor_sync(0xffffffffu, acc[i], o);
    }
    if (lane < 2) {
#pragma unroll
      for (int i = 0; i < 8; i++) red[warp][lane * 8 + i] = acc[i];
    }
    __syncthreads();
    if (tid < 16) {
      float s = 0.f;
#pragma unroll
      for (int w8 = 0; w8 < 8; w8++) s += red[w8][tid];
      g_colsum[out + tid] = s;
    }
  }
  if (b < 128) {
#pragma unroll
    for (int j = 0; j < 2; j++) {
      const int row = b * 16 + warp * 2 + j;
      const uint4* p = reinterpret_cast<const uint4*>(x + (size_t)row * D_ + lane * 16);
      uint4 v0 = __ldg(p), v1 = __ldg(p + 1);
      uint32_t u[8] = {v0.x, v0.y, v0.z, v0.w, v1.x, v1.y, v1.z, v1.w};
      float s = 0.f, q = 0.f;
#pragma unroll
      for (int i = 0; i < 8; i++) {
        float a = bf_lo(u[i]), c = bf_hi(u[i]);
        s += a + c; q = fmaf(a, a, fmaf(c, c, q));
      }
      s += __shfl_xor_sync(0xffffffffu, s, 1); q += __shfl_xor_sync(0xffffffffu, q, 1);
      s += __shfl_xor_sync(0xffffffffu, s, 2); q += __shfl_xor_sync(0xffffffffu, q, 2);
      if ((lane & 3) == 0) g_stats[row * 8 + (lane >> 2)] = make_float2(s, q);
    }
  }
}

template <int PITCH>
__device__ __forceinline__ void g1_store_item(uint32_t stage, int type, int head, int hh, int trow  , int token,
                                              unsigned* nrm) {
  const uint32_t a = stage + trow * PITCH + hh * 32;
  uint4 v0 = lds128(a), v1 = lds128(a + 16);
  if (type == 0) {
    uint4* dst = g_q + (size_t)head * (S_ * 2) + (token >> 3) * 16 + (token & 7);
    dst[0] = v0; dst[8] = v1;
    uint32_t u[8] = {v0.x, v0.y, v0.z, v0.w, v1.x, v1.y, v1.z, v1.w};
    float n = 0.f;
#pragma unroll
    for (int i = 0; i < 8; i++) {
      float2 f = __half22float2(*reinterpret_cast<__half2*>(&u[i]));
      n = fmaf(f.x, f.x, fmaf(f.y, f.y, n));
    }
    unsigned m = __reduce_max_sync(0xffffffffu, __float_as_uint(n) & 0x7fffffffu);
    if ((threadIdx.x & 31) == 0) atomicMax(nrm + head * 4 + (token >> 9), m);
  } else {
    const int pos = (token & 31) * 64 + (token >> 5);
    if (type == 1) {
      uint4 p0 = make_uint4(0, 0, 0, 0), p1 = p0;
      if (token & 31) { p0 = lds128(a - PITCH); p1 = lds128(a - PITCH + 16); }
      uint32_t u[8] = {v0.x, v0.y, v0.z, v0.w, v1.x, v1.y, v1.z, v1.w};
      uint32_t w[8] = {p0.x, p0.y, p0.z, p0.w, p1.x, p1.y, p1.z, p1.w};
      uint32_t d[8];
      float n = 0.f;
#pragma unroll
      for (int i = 0; i < 8; i++) {
        float lo = bf_lo(u[i]), hi = bf_hi(u[i]);
        n = fmaf(lo, lo, fmaf(hi, hi, n));
        d[i] = pack_f16(lo - bf_lo(w[i]), hi - bf_hi(w[i]));
      }
      uint4* dst = g_k + (size_t)head * (S_ * 2) + (pos >> 3) * 16 + (pos & 7);
      dst[0] = make_uint4(d[0], d[1], d[2], d[3]); dst[8] = make_uint4(d[4], d[5], d[6], d[7]);
      unsigned m = __reduce_max_sync(0xffffffffu, __float_as_uint(n) & 0x7fffffffu);
      if ((threadIdx.x & 31) == 0) atomicMax(nrm + 128 + head, m);
    } else {
      uint4* dst = g_v + (size_t)head * (S_ * 2) + pos;
      dst[0] = v0; dst[S_] = v1;
    }
  }
}

template <int NB, int PITCH>
__device__ __forceinline__ void g1_stage(const float (&acc)[NB * 4], uint32_t stage_row0  ,
                                         const float* cs  , int qblocks  ,
                                         float mu0, float rs0, float mu1, float rs1) {
  const int lane = threadIdx.x & 31;
  const uint32_t addr = stage_row0 + (lane & 15) * PITCH + (lane >> 4) * 16;
#pragma unroll
  for (int j = 0; j < NB; j += 2) {
    uint32_t r[4];
    const bool isq = j < qblocks;
    const float f0 = isq ? rs0 * QSCALE : rs0, f1 = isq ? rs1 * QSCALE : rs1;
#pragma unroll
    for (int e = 0; e < 2; e++) {
      float2 c = *reinterpret_cast<const float2*>(cs + (j + e) * 8 + (lane & 3) * 2);
      float a0 = fmaf(-mu0, c.x, acc[(j + e) * 4 + 0]) * f0, a1 = fmaf(-mu0, c.y, acc[(j + e) * 4 + 1]) * f0;
      float a2 = fmaf(-mu1, c.x, acc[(j + e) * 4 + 2]) * f1, a3 = fmaf(-mu1, c.y, acc[(j + e) * 4 + 3]) * f1;
      r[e * 2 + 0] = isq ? pack_f16(a0, a1) : pack_bf16(a0, a1);
      r[e * 2 + 1] = isq ? pack_f16(a2, a3) : pack_bf16(a2, a3);
    }
    stsm4(addr + j * 16, r[0], r[1], r[2], r[3]);
  }
}

constexpr int G1A_NS = 5, G1A_STAGE = 16384 + 3 * 8192, G1A_PITCH = 400;
constexpr int G1A_SMEM = G1A_NS * G1A_STAGE + 1024 + 192 * 4 + 128;
template <bool FIRST>
__global__ void __launch_bounds__(288, 1) g1a_kernel(const __grid_constant__ CUtensorMap mx, const __grid_constant__ CUtensorMap mw, int layer) {
  extern __shared__ uint8_t smem_raw[];
  const uint32_t sbase = (s2u(smem_raw) + 1023) & ~1023u;
  const uint32_t s_cs = sbase + G1A_NS * G1A_STAGE, s_bar = s_cs + 192 * 4;
  float* cs = reinterpret_cast<float*>(smem_raw + (s_cs - s2u(smem_raw)));
  const int tid = threadIdx.x, warp = tid >> 5, lane = tid & 31;
  const int nb = blockIdx.x & 7, mb = blockIdx.x >> 3;
  if (tid == 0) {
    for (int i = 0; i < G1A_NS; i++) { mbar_init(s_bar + i * 8, 1); mbar_init(s_bar + 40 + i * 8, 2); }
    fence_bar_init();
  }
  __syncthreads();
  if (warp == 8) {
    if (lane == 0) {
      for (int c = 0; c < G1A_NS; c++) {
        const uint32_t st = sbase + c * G1A_STAGE, bar = s_bar + c * 8;
        mbar_expect(bar, G1A_STAGE);
        if (FIRST) tma_load(st, &mx, c * 64, mb * 128, bar);
        for (int j = 0; j < 3; j++) tma_load(st + 16384 + j * 8192, &mw, nb * 192 + j * 64, c * 64, bar);
      }
      if (!FIRST) {
        pdl_wait();
        for (int c = 0; c < G1A_NS; c++) tma_load(sbase + c * G1A_STAGE, &mx, c * 64, mb * 128, s_bar + c * 8);
      }
      for (int c = G1A_NS; c < 8; c++) {
        const int s = c - G1A_NS;
        const uint32_t st = sbase + s * G1A_STAGE, bar = s_bar + s * 8;
        mbar_wait(s_bar + 40 + s * 8, 0);
        mbar_expect(bar, G1A_STAGE);
        tma_load(st, &mx, c * 64, mb * 128, bar);
        for (int j = 0; j < 3; j++) tma_load(st + 16384 + j * 8192, &mw, nb * 192 + j * 64, c * 64, bar);
      }
    }
    return;
  }
  const int wg = warp >> 2;
  float mu0, rs0, mu1, rs1;
  const int row0 = mb * 128 + wg * 64 + (warp & 3) * 16 + (lane >> 2);
  if (!FIRST) {
    pdl_wait();
    pdl_launch();
    if (tid < 192) cs[tid] = __ldcg(g_colsum + nb * 192 + tid);
    row_stats(row0, mu0, rs0); row_stats(row0 + 8, mu1, rs1);
  }
  float acc[96];
#pragma unroll
  for (int i = 0; i < 96; i++) acc[i] = 0.f;
  pin(acc);
#pragma unroll 1
  for (int c = 0; c < 8; c++) {
    const int s = c < G1A_NS ? c : c - G1A_NS;
    mbar_wait(s_bar + s * 8, c >= G1A_NS);
    const uint32_t st = sbase + s * G1A_STAGE;
    const uint64_t da = mkdesc(st + wg * 8192, 16, 1024, 1), db = mkdesc(st + 16384, 8192, 1024, 1);
    wg_fence();
#pragma unroll
    for (int k = 0; k < 4; k++) wgmma_gemm_n192(acc, da + k * 2, db + k * 128);
    wg_commit();
    if (c >= 1 && c <= 3) { wg_wait<1>(); if ((tid & 127) == 0) mbar_arrive(s_bar + 40 + (c - 1) * 8); }
  }
  wg_wait<0>();
  pin(acc);
  if (FIRST) {
    pdl_wait();
    pdl_launch();
    if (tid < 192) cs[tid] = __ldcg(g_colsum + nb * 192 + tid);
    row_stats(row0, mu0, rs0); row_stats(row0 + 8, mu1, rs1);
  }
  named_sync(1, 256);
  const int qb = min(max(512 - nb * 192, 0), 192) >> 3;
  g1_stage<24, G1A_PITCH>(acc, sbase + (wg * 64 + (warp & 3) * 16) * G1A_PITCH, cs, qb, mu0, rs0, mu1, rs1);
  named_sync(1, 256);
  unsigned* nrm = g_nrm + layer * 160;
#pragma unroll 2
  for (int it = 0; it < 6; it++) {
    const int item = warp + it * 8, hh = item >> 2, tg = item & 3;
    const int hg = nb * 12 + hh, type = hg >> 5;
    const int trow = type == 0 ? tg * 32 + lane : (lane >> 3) * 32 + tg * 8 + (lane & 7);
    g1_store_item<G1A_PITCH>(sbase, type, hg & 31, hh, trow, mb * 128 + trow, nrm);
  }
}

constexpr int G1B_NS = 6, G1B_STAGE = 4 * 8192, G1B_PITCH = 304;
constexpr int G1B_SMEM = G1B_NS * G1B_STAGE + 1024 + 144 * 4 + 128;
__global__ void __launch_bounds__(288, 1) g1b_kernel(const __grid_constant__ CUtensorMap mx, const __grid_constant__ CUtensorMap mwq,
                                                     const __grid_constant__ CUtensorMap mwk, const __grid_constant__ CUtensorMap mwv, int layer) {
  extern __shared__ uint8_t smem_raw[];
  const uint32_t sbase = (s2u(smem_raw) + 1023) & ~1023u;
  const uint32_t s_cs = sbase + G1B_NS * G1B_STAGE, s_bar = s_cs + 144 * 4;
  float* cs = reinterpret_cast<float*>(smem_raw + (s_cs - s2u(smem_raw)));
  const int tid = threadIdx.x, warp = tid >> 5, lane = tid & 31;
  const int nb = blockIdx.x & 3, mb = blockIdx.x >> 2;
  const bool extra = nb < 2;
  if (tid == 0) {
    for (int i = 0; i < G1B_NS; i++) { mbar_init(s_bar + i * 8, 1); mbar_init(s_bar + 48 + i * 8, 2); }
    fence_bar_init();
  }
  __syncthreads();
  if (warp == 8) {
    if (lane == 0) {
      const CUtensorMap* me = nb == 0 ? &mwk : &mwv;
      const uint32_t bytes = extra ? 4 * 8192 : 3 * 8192;
      for (int c = 0; c < G1B_NS; c++) {
        const uint32_t st = sbase + c * G1B_STAGE, bar = s_bar + c * 8;
        mbar_expect(bar, bytes);
        for (int j = 0; j < 2; j++) tma_load(st + 8192 + j * 8192, &mwq, nb * 128 + j * 64, c * 64, bar);
        if (extra) tma_load(st + 3 * 8192, me, 0, c * 64, bar);
      }
      pdl_wait();
      for (int c = 0; c < G1B_NS; c++) tma_load(sbase + c * G1B_STAGE, &mx, c * 64, mb * 64, s_bar + c * 8);
      for (int c = G1B_NS; c < 8; c++) {
        const int s = c - G1B_NS;
        const uint32_t st = sbase + s * G1B_STAGE, bar = s_bar + s * 8;
        mbar_wait(s_bar + 48 + s * 8, 0);
        mbar_expect(bar, bytes);
        tma_load(st, &mx, c * 64, mb * 64, bar);
        for (int j = 0; j < 2; j++) tma_load(st + 8192 + j * 8192, &mwq, nb * 128 + j * 64, c * 64, bar);
        if (extra) tma_load(st + 3 * 8192, me, 0, c * 64, bar);
      }
    }
    return;
  }
  const int wg = warp >> 2;
  float mu0, rs0, mu1, rs1;
  const int row0 = mb * 64 + (warp & 3) * 16 + (lane >> 2);
  pdl_wait();
  pdl_launch();
  if (tid < 128) cs[tid] = __ldcg(g_colsum + 1536 + nb * 128 + tid);
  else if (tid < 144) cs[tid] = __ldcg(g_colsum + 2048 + (nb & 1) * 16 + (tid - 128));
  row_stats(row0, mu0, rs0); row_stats(row0 + 8, mu1, rs1);
  const uint32_t srow = sbase + (warp & 3) * 16 * G1B_PITCH + wg * 128;
  if (wg == 1 && extra) {
    float acc[40];
#pragma unroll
    for (int i = 0; i < 40; i++) acc[i] = 0.f;
    pin(acc);
#pragma unroll 1
    for (int c = 0; c < 8; c++) {
      const int s = c < G1B_NS ? c : c - G1B_NS;
      mbar_wait(s_bar + s * 8, c >= G1B_NS);
      const uint32_t st = sbase + s * G1B_STAGE;
      const uint64_t da = mkdesc(st, 16, 1024, 1), db = mkdesc(st + 16384, 8192, 1024, 1);
      wg_fence();
#pragma unroll
      for (int k = 0; k < 4; k++) wgmma_gemm_n80(acc, da + k * 2, db + k * 128);
      wg_commit();
      if (c >= 1 && c <= 2) { wg_wait<1>(); if ((tid & 127) == 0) mbar_arrive(s_bar + 48 + (c - 1) * 8); }
    }
    wg_wait<0>();
    pin(acc);
    named_sync(1, 256);
    g1_stage<10, G1B_PITCH>(acc, srow, cs + 64, 8, mu0, rs0, mu1, rs1);
  } else {
    float acc[32];
#pragma unroll
    for (int i = 0; i < 32; i++) acc[i] = 0.f;
    pin(acc);
#pragma unroll 1
    for (int c = 0; c < 8; c++) {
      const int s = c < G1B_NS ? c : c - G1B_NS;
      mbar_wait(s_bar + s * 8, c >= G1B_NS);
      const uint32_t st = sbase + s * G1B_STAGE;
      const uint64_t da = mkdesc(st, 16, 1024, 1), db = mkdesc(st + 8192 + wg * 8192, 8192, 1024, 1);
      wg_fence();
#pragma unroll
      for (int k = 0; k < 4; k++) wgmma_gemm_n64(acc, da + k * 2, db + k * 128);
      wg_commit();
      if (c >= 1 && c <= 2) { wg_wait<1>(); if ((tid & 127) == 0) mbar_arrive(s_bar + 48 + (c - 1) * 8); }
    }
    wg_wait<0>();
    pin(acc);
    named_sync(1, 256);
    g1_stage<8, G1B_PITCH>(acc, srow, cs + wg * 64, 8, mu0, rs0, mu1, rs1);
  }
  named_sync(1, 256);
  unsigned* nrm = g_nrm + layer * 160;
#pragma unroll
  for (int it = 0; it < 2; it++) {
    const int item = warp + it * 8, hh = item >> 1, trow = (item & 1) * 32 + lane;
    g1_store_item<G1B_PITCH>(sbase, 0, nb * 8 + hh, hh, trow, mb * 64 + trow, nrm);
  }
  if (extra && warp < 2) {
    const int trow = (lane >> 4) * 32 + warp * 16 + (lane & 15);
    g1_store_item<G1B_PITCH>(sbase, 1 + nb, 0, 8, trow, mb * 64 + trow, nrm);
  }
}

constexpr int G2_SMEM = 8 * 3 * 8192 + 1024 + 128;
template <bool LAST>
__global__ void __launch_bounds__(288, 1) g2_kernel(const __grid_constant__ CUtensorMap mo, const __grid_constant__ CUtensorMap mw,
                                                    const __nv_bfloat16* xin, __nv_bfloat16* xout) {
  extern __shared__ uint8_t smem_raw[];
  const uint32_t sbase = (s2u(smem_raw) + 1023) & ~1023u;
  const uint32_t s_bar = sbase + 8 * 3 * 8192;
  const int tid = threadIdx.x, warp = tid >> 5, lane = tid & 31;
  const int nb = blockIdx.x & 3, mb = blockIdx.x >> 2;
  if (tid == 0) {
    for (int i = 0; i < 8; i++) mbar_init(s_bar + i * 8, 1);
    fence_bar_init();
  }
  __syncthreads();
  if (warp == 8) {
    if (lane == 0) {
      for (int c = 0; c < 8; c++) {
        const uint32_t st = sbase + c * 24576, bar = s_bar + c * 8;
        mbar_expect(bar, 24576);
        for (int j = 0; j < 2; j++) tma_load(st + 8192 + j * 8192, &mw, nb * 128 + j * 64, c * 64, bar);
      }
      pdl_wait();
      for (int c = 0; c < 8; c++) tma_load(sbase + c * 24576, &mo, c * 64, mb * 64, s_bar + c * 8);
    }
    return;
  }
  const int wg = warp >> 2;
  const int row0 = mb * 64 + (warp & 3) * 16 + (lane >> 2), col0 = nb * 128 + wg * 64 + (lane & 3) * 2;
  uint32_t res[16];
#pragma unroll
  for (int j = 0; j < 8; j++) {
    res[2 * j] = __ldcg(reinterpret_cast<const uint32_t*>(xin + (size_t)row0 * D_ + col0 + j * 8));
    res[2 * j + 1] = __ldcg(reinterpret_cast<const uint32_t*>(xin + (size_t)(row0 + 8) * D_ + col0 + j * 8));
  }
  pdl_wait();
  pdl_launch();
  float acc[32];
#pragma unroll
  for (int i = 0; i < 32; i++) acc[i] = 0.f;
  pin(acc);
#pragma unroll 1
  for (int c = 0; c < 8; c++) {
    mbar_wait(s_bar + c * 8, 0);
    const uint32_t st = sbase + c * 24576;
    const uint64_t da = mkdesc(st, 16, 1024, 1), db = mkdesc(st + 8192 + wg * 8192, 8192, 1024, 1);
    wg_fence();
#pragma unroll
    for (int k = 0; k < 4; k++) wgmma_gemm_n64(acc, da + k * 2, db + k * 128);
    wg_commit();
  }
  wg_wait<0>();
  pin(acc);
  float s0 = 0.f, q0 = 0.f, s1 = 0.f, q1 = 0.f;
#pragma unroll
  for (int j = 0; j < 8; j++) {
    uint32_t t0 = pack_bf16(acc[4 * j], acc[4 * j + 1]), t1 = pack_bf16(acc[4 * j + 2], acc[4 * j + 3]);
    uint32_t y0 = pack_bf16(bf_lo(t0) + bf_lo(res[2 * j]), bf_hi(t0) + bf_hi(res[2 * j]));
    uint32_t y1 = pack_bf16(bf_lo(t1) + bf_lo(res[2 * j + 1]), bf_hi(t1) + bf_hi(res[2 * j + 1]));
    *reinterpret_cast<uint32_t*>(xout + (size_t)row0 * D_ + col0 + j * 8) = y0;
    *reinterpret_cast<uint32_t*>(xout + (size_t)(row0 + 8) * D_ + col0 + j * 8) = y1;
    if (!LAST) {
      float a = bf_lo(y0), b = bf_hi(y0), c = bf_lo(y1), d = bf_hi(y1);
      s0 += a + b; q0 = fmaf(a, a, fmaf(b, b, q0));
      s1 += c + d; q1 = fmaf(c, c, fmaf(d, d, q1));
    }
  }
  if (!LAST) {
#pragma unroll
    for (int o = 1; o < 4; o <<= 1) {
      s0 += __shfl_xor_sync(0xffffffffu, s0, o); q0 += __shfl_xor_sync(0xffffffffu, q0, o);
      s1 += __shfl_xor_sync(0xffffffffu, s1, o); q1 += __shfl_xor_sync(0xffffffffu, q1, o);
    }
    if ((lane & 3) == 0) {
      g_stats[row0 * 8 + nb * 2 + wg] = make_float2(s0, q0);
      g_stats[(row0 + 8) * 8 + nb * 2 + wg] = make_float2(s1, q1);
    }
  }
}

constexpr uint32_t MUFU_MASK = 0xF800u;
constexpr float EXP_MAGIC = 383.0f + 0.65f / 128.0f;
constexpr uint32_t POLY_A = 0x5a835a83u, POLY_B = 0x92a192a1u, POLY_C = 0x800b800bu;
constexpr float SCORE_LIMIT = 118.f;

__device__ __forceinline__ void exp_step(const float (&s)[32], uint32_t (&p)[16], uint32_t pb) {
#pragma unroll
  for (int i = 0; i < 16; i++) {
    if ((MUFU_MASK >> i) & 1) {
      float a, b;
      asm("ex2.approx.ftz.f32 %0, %1;" : "=f"(a) : "f"(s[2 * i]));
      asm("ex2.approx.ftz.f32 %0, %1;" : "=f"(b) : "f"(s[2 * i + 1]));
      p[i] = pack_bf16(a, b);
    } else {
      uint32_t z, u, h;
      asm("prmt.b32 %0, %1, %2, 0x6521;" : "=r"(z) : "r"(__float_as_uint(s[2 * i])), "r"(__float_as_uint(s[2 * i + 1])));
      asm("fma.rn.f16x2 %0, %1, %2, %3;" : "=r"(u) : "r"(z & 0x007f007fu), "r"(POLY_A), "r"(pb));
      asm("fma.rn.f16x2 %0, %1, %1, %2;" : "=r"(h) : "r"(u), "r"(POLY_C));
      p[i] = z - h;
    }
  }
}

constexpr int AT_K = 0, AT_V = 65536, AT_Q = 65536 + 98304, AT_BAR = AT_Q + 16384;
constexpr int ATT_SMEM = AT_BAR + 128 + 1024;

template <bool PV>
__device__ __forceinline__ void att_step(float (&s)[32], float (&o)[12], uint32_t (&pin_)[16], uint32_t (&pout)[16], uint64_t dq,
                                         uint64_t dk, uint64_t dv, uint32_t pb) {
  pin(s); pin(pin_);
  wg_fence();
  wgmma_qk_n64(s, dq, dk);
  wg_commit();
  if (PV) {
#pragma unroll
    for (int j = 0; j < 4; j++) wgmma_pv_n24(o, pin_[4 * j], pin_[4 * j + 1], pin_[4 * j + 2], pin_[4 * j + 3], dv + j * 16);
    wg_commit();
    wg_wait<1>();
  } else {
    wg_wait<0>();
  }
  pin(s);
  exp_step(s, pout, pb);
  pin(pout);
}

struct AttFb {
  const __nv_bfloat16* x;
  const __nv_bfloat16* wq; const __nv_bfloat16* wk;
  int ldq, ldk, khead;
};

__device__ __noinline__ void att_fallback(const AttFb fb, uint8_t* sm, int head, int quarter) {
  const int tid = threadIdx.x;
  __nv_bfloat16* sk = reinterpret_cast<__nv_bfloat16*>(sm + AT_K);
  const __nv_bfloat16* sv = reinterpret_cast<const __nv_bfloat16*>(sm + AT_V);
  float q[16];
  for (int it = 0; it < 5; it++) {
    const bool isq = it == 4;
    const int token = isq ? quarter * 512 + tid : it * 512 + tid;
    const __nv_bfloat16* w = isq ? fb.wq + head * 16 : fb.wk + head * fb.khead;
    const int ld = isq ? fb.ldq : fb.ldk;
    float mu, rs;
    row_stats(token, mu, rs);
#pragma unroll
    for (int d = 0; d < 16; d++) q[d] = 0.f;
    for (int k = 0; k < D_; k++) {
      const float xn = __bfloat162float(__float2bfloat16((__bfloat162float(fb.x[(size_t)token * D_ + k]) - mu) * rs));
#pragma unroll
      for (int d = 0; d < 16; d++) q[d] = fmaf(xn, __bfloat162float(w[(size_t)k * ld + d]), q[d]);
    }
    if (!isq) {
      const int pos = (token & 31) * 64 + (token >> 5);
#pragma unroll
      for (int d = 0; d < 16; d++) sk[pos * 16 + d] = __float2bfloat16(q[d]);
    }
  }
#pragma unroll
  for (int d = 0; d < 16; d++) q[d] = __bfloat162float(__float2bfloat16(q[d]));
  __syncthreads();
  float m = -INFINITY, l = 0.f, o[16];
#pragma unroll
  for (int d = 0; d < 16; d++) o[d] = 0.f;
  for (int j = 0; j < S_; j++) {
    float sc = 0.f;
#pragma unroll
    for (int d = 0; d < 16; d++) sc = fmaf(q[d], __bfloat162float(sk[j * 16 + d]), sc);
    sc *= 0.25f;
    if (sc > m) {
      const float a = __expf(m - sc);
      l *= a;
#pragma unroll
      for (int d = 0; d < 16; d++) o[d] *= a;
      m = sc;
    }
    const float p = __expf(sc - m);
    l += p;
#pragma unroll
    for (int d = 0; d < 16; d++) o[d] = fmaf(p, __bfloat162float(sv[(d >> 3) * (S_ * 8) + j * 8 + (d & 7)]), o[d]);
  }
  const float inv = 1.f / l;
  __nv_bfloat16* dst = g_o + (size_t)(quarter * 512 + tid) * D_ + head * 16;
#pragma unroll
  for (int d = 0; d < 16; d++) dst[d] = __float2bfloat16(o[d] * inv);
}

__global__ void __launch_bounds__(512, 1) att_kernel(int layer, int kvstride  , const AttFb fb) {
  extern __shared__ uint8_t smem_raw[];
  const uint32_t sbase = (s2u(smem_raw) + 1023) & ~1023u;
  uint8_t* sm = smem_raw + (sbase - s2u(smem_raw));
  const uint32_t s_bar = sbase + AT_BAR;
  const int tid = threadIdx.x, warp = tid >> 5, lane = tid & 31;
  const int head = blockIdx.x >> 2, quarter = blockIdx.x & 3, kvh = head * kvstride;
  if (tid == 0) {
    mbar_init(s_bar, 4);
    for (int i = 1; i < 5; i++) mbar_init(s_bar + i * 8, 3);
    mbar_init(s_bar + 40, 1);
    fence_bar_init();
  }
#pragma unroll
  for (int i = 0; i < 4; i++)
    *reinterpret_cast<uint4*>(sm + AT_V + 65536 + (i * 512 + tid) * 16) = make_uint4(0x3f803f80u, 0x3f803f80u, 0x3f803f80u, 0x3f803f80u);
  fence_async_smem();
  __syncthreads();
  pdl_wait();
  if (lane == 0) {
    const uint8_t* gq = reinterpret_cast<const uint8_t*>(g_q) + (size_t)head * 65536 + quarter * 16384;
    const uint8_t* gk = reinterpret_cast<const uint8_t*>(g_k) + (size_t)kvh * 65536;
    const uint8_t* gv = reinterpret_cast<const uint8_t*>(g_v) + (size_t)kvh * 65536;
    if (warp == 15) {
      mbar_expect(s_bar, 8192); bulk_load(sbase + AT_Q, gq, 8192, s_bar);
      mbar_expect(s_bar + 40, 8192); bulk_load(sbase + AT_Q + 8192, gq + 8192, 8192, s_bar + 40);
    } else {
      const int c = warp / 3, w = warp - c * 3;
      const int t0 = c == 0 ? 0 : (c == 1 ? 2 : (c - 1) * 8), nt = c == 0 ? 2 : (c == 1 ? 6 : 8);
      const uint32_t bar = s_bar + c * 8;
      if (w == 0) { mbar_expect(bar, nt * 2048); bulk_load(sbase + AT_K + t0 * 2048, gk + t0 * 2048, nt * 2048, bar); }
      else {
        const int off = (w - 1) * 32768 + t0 * 1024;
        mbar_expect(bar, nt * 1024); bulk_load(sbase + AT_V + off, gv + off, nt * 1024, bar);
      }
    }
  }
  pdl_launch();
  const float qn = __uint_as_float(__ldcg(g_nrm + layer * 160 + head * 4 + quarter));
  const float kn = __uint_as_float(__ldcg(g_nrm + layer * 160 + 128 + kvh));
  int bad = !(qn * kn <= SCORE_LIMIT * SCORE_LIMIT && qn <= 1.0e6f && kn <= 1.0e6f);
  if (!bad) {
    const int wg = __shfl_sync(0xffffffffu, warp >> 2, 0);
    uint32_t pb = POLY_B;
    asm volatile("" : "+r"(pb));
#pragma unroll 1
    for (int rnd = 0; rnd < 2; rnd++) {
      float s[32], o[12];
      uint32_t p0[16], p1[16];
#pragma unroll
      for (int i = 0; i < 32; i++) s[i] = ((MUFU_MASK >> (i >> 1)) & 1) ? 0.f : EXP_MAGIC;
#pragma unroll
      for (int i = 0; i < 12; i++) o[i] = 0.f;
#pragma unroll
      for (int i = 0; i < 16; i++) p1[i] = 0u;
      const uint64_t dq = mkdesc(sbase + AT_Q + rnd * 8192 + wg * 2048, 128, 256, 0);
      uint64_t dk = mkdesc(sbase + AT_K, 128, 256, 0), dv = mkdesc(sbase + AT_V, 128, 32768, 0);
      pin(o);
      mbar_wait(rnd ? s_bar + 40 : s_bar, 0);
      att_step<false>(s, o, p1, p0, dq, dk, dv, pb);
      att_step<true>(s, o, p0, p1, dq, dk + 128, dv, pb);
      wg_wait<0>();
      mbar_wait(s_bar + 8, 0);
#pragma unroll
      for (int u = 2; u < 8; u += 2) {
        att_step<true>(s, o, p1, p0, dq, dk + u * 128, dv + (u - 1) * 64, pb);
        att_step<true>(s, o, p0, p1, dq, dk + (u + 1) * 128, dv + u * 64, pb);
      }
      wg_wait<0>();
#pragma unroll 1
      for (int b = 1; b < 4; b++) {
        dk += 8 * 128; dv += 8 * 64;
        mbar_wait(s_bar + 8 + b * 8, 0);
#pragma unroll
        for (int u = 0; u < 8; u += 2) {
          att_step<true>(s, o, p1, p0, dq, dk + u * 128, dv + (u - 1) * 64, pb);
          att_step<true>(s, o, p0, p1, dq, dk + (u + 1) * 128, dv + u * 64, pb);
        }
        wg_wait<0>();
      }
      pin(p1);
      wg_fence();
#pragma unroll
      for (int j = 0; j < 4; j++) wgmma_pv_n24(o, p1[4 * j], p1[4 * j + 1], p1[4 * j + 2], p1[4 * j + 3], dv + 7 * 64 + j * 16);
      wg_commit();
      wg_wait<0>();
      pin(o);
      const float l0 = o[8], l1 = o[10];
      const float i0 = __frcp_rn(l0), i1 = __frcp_rn(l1);
      float mx = 0.f;
#pragma unroll
      for (int i = 0; i < 8; i++) mx += fabsf(o[i]);
      if (!(l0 >= 1e-18f && l0 <= 1e37f && l1 >= 1e-18f && l1 <= 1e37f && mx <= 3e38f)) bad = 1;
      __nv_bfloat16* dst = g_o + (size_t)(quarter * 512 + rnd * 256 + wg * 64 + (warp & 3) * 16 + (lane >> 2)) * D_ + head * 16 + (lane & 3) * 2;
      *reinterpret_cast<uint32_t*>(dst) = pack_bf16(o[0] * i0, o[1] * i0);
      *reinterpret_cast<uint32_t*>(dst + 8) = pack_bf16(o[4] * i0, o[5] * i0);
      *reinterpret_cast<uint32_t*>(dst + 8 * D_) = pack_bf16(o[2] * i1, o[3] * i1);
      *reinterpret_cast<uint32_t*>(dst + 8 * D_ + 8) = pack_bf16(o[6] * i1, o[7] * i1);
    }
  }
  if (__syncthreads_or(bad)) {
    for (int i = 0; i < 6; i++) mbar_wait(s_bar + i * 8, 0);
    __syncthreads();
    att_fallback(fb, sm, head, quarter);
  }
}

typedef CUresult (*EncodeFn)(CUtensorMap*, CUtensorMapDataType, cuuint32_t, void*, const cuuint64_t*, const cuuint64_t*,
                             const cuuint32_t*, const cuuint32_t*, CUtensorMapInterleave, CUtensorMapSwizzle,
                             CUtensorMapL2promotion, CUtensorMapFloatOOBfill);

void make_map(EncodeFn enc, CUtensorMap* m, const void* p, int rows, int cols, int box_rows) {
  cuuint64_t dim[2] = {(cuuint64_t)cols, (cuuint64_t)rows};
  cuuint64_t str[1] = {(cuuint64_t)cols * 2};
  cuuint32_t box[2] = {64, (cuuint32_t)box_rows};
  cuuint32_t es[2] = {1, 1};
  enc(m, CU_TENSOR_MAP_DATA_TYPE_BFLOAT16, 2, const_cast<void*>(p), dim, str, box, es, CU_TENSOR_MAP_INTERLEAVE_NONE,
      CU_TENSOR_MAP_SWIZZLE_128B, CU_TENSOR_MAP_L2_PROMOTION_L2_128B, CU_TENSOR_MAP_FLOAT_OOB_FILL_NONE);
}

template <typename... KA, typename... A>
void launch(void (*k)(KA...), int grid, int block, int smem, bool pdl, A... args) {
  cudaLaunchConfig_t cfg = {};
  cfg.gridDim = dim3(grid); cfg.blockDim = dim3(block); cfg.dynamicSmemBytes = smem; cfg.stream = cudaStreamPerThread;
  cudaLaunchAttribute at[1];
  at[0].id = cudaLaunchAttributeProgrammaticStreamSerialization;
  at[0].val.programmaticStreamSerializationAllowed = 1;
  cfg.attrs = at; cfg.numAttrs = pdl ? 1 : 0;
  cudaLaunchKernelEx(&cfg, k, KA(args)...);
}

struct HostState {
  bool init;
  const void* in[8];
  CUtensorMap x0_128, x_128, x_64, o_64, wqkv, wq, wk, wv, woa, wob;
  __nv_bfloat16* gx;
};
HostState hs;

}

extern "C" void kernel_launch(void* const* d_in, const int* in_sizes, int n_in, void* d_out, int out_size) {
  const __nv_bfloat16* A_x = (const __nv_bfloat16*)d_in[0];
  const __nv_bfloat16* A_wqkv = (const __nv_bfloat16*)d_in[1];
  const __nv_bfloat16* A_wo = (const __nv_bfloat16*)d_in[2];
  const __nv_bfloat16* B_wq = (const __nv_bfloat16*)d_in[4];
  const __nv_bfloat16* B_wk = (const __nv_bfloat16*)d_in[5];
  const __nv_bfloat16* B_wv = (const __nv_bfloat16*)d_in[6];
  const __nv_bfloat16* B_wo = (const __nv_bfloat16*)d_in[7];
  __nv_bfloat16* out = (__nv_bfloat16*)d_out;
  bool same = hs.init;
  for (int i = 0; i < 8; i++) same = same && hs.in[i] == d_in[i];
  if (!same) {
    void* fn = nullptr;
    cudaDriverEntryPointQueryResult qr;
    cudaGetDriverEntryPoint("cuTensorMapEncodeTiled", &fn, cudaEnableDefault, &qr);
    EncodeFn enc = (EncodeFn)fn;
    void *px, *po;
    cudaGetSymbolAddress(&px, g_x);
    cudaGetSymbolAddress(&po, g_o);
    hs.gx = (__nv_bfloat16*)px;
    make_map(enc, &hs.x0_128, A_x, S_, D_, 128);
    make_map(enc, &hs.x_128, px, S_, D_, 128);
    make_map(enc, &hs.x_64, px, S_, D_, 64);
    make_map(enc, &hs.o_64, po, S_, D_, 64);
    make_map(enc, &hs.wqkv, A_wqkv, D_, 1536, 64);
    make_map(enc, &hs.wq, B_wq, D_, 512, 64);
    make_map(enc, &hs.wk, B_wk, D_, 16, 64);
    make_map(enc, &hs.wv, B_wv, D_, 16, 64);
    make_map(enc, &hs.woa, A_wo, D_, D_, 64);
    make_map(enc, &hs.wob, B_wo, D_, D_, 64);
    cudaFuncSetAttribute(g1a_kernel<true>, cudaFuncAttributeMaxDynamicSharedMemorySize, G1A_SMEM);
    cudaFuncSetAttribute(g1a_kernel<false>, cudaFuncAttributeMaxDynamicSharedMemorySize, G1A_SMEM);
    cudaFuncSetAttribute(g1b_kernel, cudaFuncAttributeMaxDynamicSharedMemorySize, G1B_SMEM);
    cudaFuncSetAttribute(g2_kernel<false>, cudaFuncAttributeMaxDynamicSharedMemorySize, G2_SMEM);
    cudaFuncSetAttribute(g2_kernel<true>, cudaFuncAttributeMaxDynamicSharedMemorySize, G2_SMEM);
    cudaFuncSetAttribute(att_kernel, cudaFuncAttributeMaxDynamicSharedMemorySize, ATT_SMEM);
    for (int i = 0; i < 8; i++) hs.in[i] = d_in[i];
    hs.init = true;
  }
  launch(prep_kernel, 130, 256, 0, false, A_x, A_wqkv, B_wq, B_wk, B_wv);
  for (int l = 0; l < 4; l++) {
    const __nv_bfloat16* xin = l == 0 ? A_x : hs.gx;
    AttFb fb;
    fb.x = xin;
    if (l & 1) {
      launch(g1b_kernel, 128, 288, G1B_SMEM, true, hs.x_64, hs.wq, hs.wk, hs.wv, l);
      fb.wq = B_wq; fb.ldq = 512; fb.wk = B_wk; fb.ldk = 16; fb.khead = 0;
    } else {
      if (l == 0) launch(g1a_kernel<true>, 128, 288, G1A_SMEM, true, hs.x0_128, hs.wqkv, l);
      else launch(g1a_kernel<false>, 128, 288, G1A_SMEM, true, hs.x_128, hs.wqkv, l);
      fb.wq = A_wqkv; fb.ldq = 1536; fb.wk = A_wqkv + 512; fb.ldk = 1536; fb.khead = 16;
    }
    launch(att_kernel, 128, 512, ATT_SMEM, true, l, (l & 1) ? 0 : 1, fb);
    if (l == 3) launch(g2_kernel<true>, 128, 288, G2_SMEM, true, hs.o_64, hs.wob, xin, out);
    else launch(g2_kernel<false>, 128, 288, G2_SMEM, true, hs.o_64, (l & 1) ? hs.wob : hs.woa, xin, hs.gx);
  }
}
```

```cpp
#include <cuda_runtime.h>
#include <cuda_bf16.h>
#include <cuda_fp16.h>
#include <cuda.h>
#include <stdint.h>

namespace {

constexpr int S_ = 2048, D_ = 512, H_ = 32;

__device__ __align__(1024) __nv_bfloat16 g_x[3 * S_ * D_];
__device__ __align__(1024) __nv_bfloat16 g_o[S_ * D_];
__device__ __align__(1024) uint4 g_q[2 * H_ * S_ * 2];
__device__ __align__(1024) uint4 g_k[2 * H_ * S_ * 2];
__device__ __align__(1024) uint4 g_v[2 * H_ * S_ * 2];
__device__ __align__(1024) __nv_bfloat16 g_wkv[D_ * 32];
__device__ __align__(16) float2 g_stats[4 * S_ * 8];
__device__ __align__(16) float g_colsum[1536 + 512 + 64];
__device__ float g_nrm[4 * 2 * H_ * 64];
constexpr int CNT_O = 0, CNT_X = 32, CNT_KV = CNT_X + 128, CNT_Q = CNT_KV + 64, CNT_DONE = CNT_Q + 256, CNT_N = CNT_DONE + 1;
__device__ unsigned g_cnt[CNT_N];

#define TM(k, slot)
#define TC(k, slot)
#define TM2(k, slot)
__device__ __forceinline__ uint32_t s2u(const void* p) { return (uint32_t)__cvta_generic_to_shared(p); }
__device__ __forceinline__ void mbar_init(uint32_t bar, int cnt) {
  asm volatile("mbarrier.init.shared::cta.b64 [%0], %1;" ::"r"(bar), "r"(cnt) : "memory");
}
__device__ __forceinline__ void mbar_expect(uint32_t bar, uint32_t bytes) {
  asm volatile("mbarrier.arrive.expect_tx.shared::cta.b64 _, [%0], %1;" ::"r"(bar), "r"(bytes) : "memory");
}
__device__ __forceinline__ void mbar_arrive(uint32_t bar) {
  asm volatile("mbarrier.arrive.shared::cta.b64 _, [%0];" ::"r"(bar) : "memory");
}
__device__ __forceinline__ void mbar_wait(uint32_t bar, uint32_t par) {
  uint32_t ok;
  int it = 0;
  do {
    asm volatile("{.reg .pred p; mbarrier.try_wait.parity.shared::cta.b64 p, [%1], %2; selp.u32 %0,1,0,p;}"
                 : "=r"(ok) : "r"(bar), "r"(par) : "memory");
    if (++it > (1 << 24)) __trap();
  } while (!ok);
}
__device__ __forceinline__ void bulk_load(uint32_t dst, const void* src, uint32_t bytes, uint32_t bar) {
  asm volatile("cp.async.bulk.shared::cluster.global.mbarrier::complete_tx::bytes [%0], [%1], %2, [%3];"
               ::"r"(dst), "l"(src), "r"(bytes), "r"(bar) : "memory");
}
__device__ __forceinline__ void tma_load(uint32_t dst, const CUtensorMap* m, int c0, int c1, uint32_t bar) {
  asm volatile("cp.async.bulk.tensor.2d.shared::cluster.global.mbarrier::complete_tx::bytes [%0], [%1, {%3, %4}], [%2];"
               ::"r"(dst), "l"(m), "r"(bar), "r"(c0), "r"(c1) : "memory");
}
__device__ __forceinline__ bool elect_one() {
  uint32_t p;
  asm volatile("{.reg .pred q; elect.sync _|q, 0xffffffff; selp.u32 %0, 1, 0, q;}" : "=r"(p));
  return p;
}
__device__ __forceinline__ void pdl_wait() { asm volatile("griddepcontrol.wait;" ::: "memory"); }
__device__ __forceinline__ void pdl_launch() { asm volatile("griddepcontrol.launch_dependents;" ::: "memory"); }
__device__ __forceinline__ void fence_async_smem() { asm volatile("fence.proxy.async.shared::cta;" ::: "memory"); }
__device__ __forceinline__ void fence_bar_init() { asm volatile("fence.mbarrier_init.release.cluster;" ::: "memory"); }
__device__ __forceinline__ void named_sync(int id, int n) { asm volatile("bar.sync %0, %1;" ::"r"(id), "r"(n) : "memory"); }
__device__ __forceinline__ void wg_fence() { asm volatile("wgmma.fence.sync.aligned;" ::: "memory"); }
__device__ __forceinline__ void wg_commit() { asm volatile("wgmma.commit_group.sync.aligned;" ::: "memory"); }
template <int N> __device__ __forceinline__ void wg_wait() { asm volatile("wgmma.wait_group.sync.aligned %0;" ::"n"(N) : "memory"); }
template <int N> __device__ __forceinline__ void pin(float (&d)[N]) {
#pragma unroll
  for (int i = 0; i < N; i++) asm volatile("" : "+f"(d[i])::"memory");
}
template <int N> __device__ __forceinline__ void pin(uint32_t (&d)[N]) {
#pragma unroll
  for (int i = 0; i < N; i++) asm volatile("" : "+r"(d[i])::"memory");
}
__device__ __forceinline__ uint64_t mkdesc(uint32_t addr, uint32_t lbo, uint32_t sbo, uint64_t swz) {
  return (uint64_t)((addr & 0x3FFFF) >> 4) | ((uint64_t)(lbo >> 4) << 16) | ((uint64_t)(sbo >> 4) << 32) | (swz << 62);
}
__device__ __forceinline__ uint32_t pack_bf16(float lo, float hi) {
  uint32_t d; asm("cvt.rn.bf16x2.f32 %0, %1, %2;" : "=r"(d) : "f"(hi), "f"(lo)); return d;
}
__device__ __forceinline__ uint32_t pack_f16(float lo, float hi) {
  uint32_t d; asm("cvt.rn.f16x2.f32 %0, %1, %2;" : "=r"(d) : "f"(hi), "f"(lo)); return d;
}
__device__ __forceinline__ float bf_lo(uint32_t v) { return __uint_as_float(v << 16); }
__device__ __forceinline__ float bf_hi(uint32_t v) { return __uint_as_float(v & 0xffff0000u); }
__device__ __forceinline__ void stsm4(uint32_t addr, uint32_t a, uint32_t b, uint32_t c, uint32_t d) {
  asm volatile("stmatrix.sync.aligned.m8n8.x4.shared.b16 [%0], {%1,%2,%3,%4};" ::"r"(addr), "r"(a), "r"(b), "r"(c), "r"(d) : "memory");
}
__device__ __forceinline__ void ldsm4(uint32_t addr, uint32_t& a, uint32_t& b, uint32_t& c, uint32_t& d) {
  asm volatile("ldmatrix.sync.aligned.m8n8.x4.shared.b16 {%0,%1,%2,%3}, [%4];" : "=r"(a), "=r"(b), "=r"(c), "=r"(d) : "r"(addr) : "memory");
}
__device__ __forceinline__ uint32_t hadd2_bf16(uint32_t a, uint32_t b) {
  uint32_t d; asm("add.rn.bf16x2 %0, %1, %2;" : "=r"(d) : "r"(a), "r"(b)); return d;
}
__device__ __forceinline__ uint4 lds128(uint32_t addr) {
  uint4 v; asm volatile("ld.shared.v4.u32 {%0,%1,%2,%3}, [%4];" : "=r"(v.x), "=r"(v.y), "=r"(v.z), "=r"(v.w) : "r"(addr) : "memory"); return v;
}

__device__ __forceinline__ void wgmma_qk_n64(float (&d)[32], uint64_t da, uint64_t db) {
  asm volatile("wgmma.mma_async.sync.aligned.m64n64k16.f32.f16.f16 "
      "{%0,%1,%2,%3,%4,%5,%6,%7,%8,%9,%10,%11,%12,%13,%14,%15,%16,%17,%18,%19,%20,%21,%22,%23,%24,%25,%26,%27,%28,%29,%30,%31}, "
      "%32, %33, 1, 1, 1, 0, 0;"
    : "+f"(d[0]), "+f"(d[1]), "+f"(d[2]), "+f"(d[3]), "+f"(d[4]), "+f"(d[5]), "+f"(d[6]), "+f"(d[7]), "+f"(d[8]),
      "+f"(d[9]), "+f"(d[10]), "+f"(d[11]), "+f"(d[12]), "+f"(d[13]), "+f"(d[14]), "+f"(d[15]), "+f"(d[16]),
      "+f"(d[17]), "+f"(d[18]), "+f"(d[19]), "+f"(d[20]), "+f"(d[21]), "+f"(d[22]), "+f"(d[23]), "+f"(d[24]),
      "+f"(d[25]), "+f"(d[26]), "+f"(d[27]), "+f"(d[28]), "+f"(d[29]), "+f"(d[30]), "+f"(d[31])
    : "l"(da), "l"(db));
}
__device__ __forceinline__ void wgmma_pv_n24(float (&d)[12], uint32_t a0, uint32_t a1, uint32_t a2, uint32_t a3, uint64_t db) {
  asm volatile("wgmma.mma_async.sync.aligned.m64n24k16.f32.bf16.bf16 "
      "{%0,%1,%2,%3,%4,%5,%6,%7,%8,%9,%10,%11}, "
      "{%12,%13,%14,%15}, %16, 1, 1, 1, 1;"
    : "+f"(d[0]), "+f"(d[1]), "+f"(d[2]), "+f"(d[3]), "+f"(d[4]), "+f"(d[5]), "+f"(d[6]), "+f"(d[7]), "+f"(d[8]),
      "+f"(d[9]), "+f"(d[10]), "+f"(d[11])
    : "r"(a0), "r"(a1), "r"(a2), "r"(a3), "l"(db));
}
__device__ __forceinline__ void wgmma_gemm_n64(float (&d)[32], uint64_t da, uint64_t db) {
  asm volatile("wgmma.mma_async.sync.aligned.m64n64k16.f32.bf16.bf16 "
      "{%0,%1,%2,%3,%4,%5,%6,%7,%8,%9,%10,%11,%12,%13,%14,%15,%16,%17,%18,%19,%20,%21,%22,%23,%24,%25,%26,%27,%28,%29,%30,%31}, "
      "%32, %33, 1, 1, 1, 0, 1;"
    : "+f"(d[0]), "+f"(d[1]), "+f"(d[2]), "+f"(d[3]), "+f"(d[4]), "+f"(d[5]), "+f"(d[6]), "+f"(d[7]), "+f"(d[8]),
      "+f"(d[9]), "+f"(d[10]), "+f"(d[11]), "+f"(d[12]), "+f"(d[13]), "+f"(d[14]), "+f"(d[15]), "+f"(d[16]),
      "+f"(d[17]), "+f"(d[18]), "+f"(d[19]), "+f"(d[20]), "+f"(d[21]), "+f"(d[22]), "+f"(d[23]), "+f"(d[24]),
      "+f"(d[25]), "+f"(d[26]), "+f"(d[27]), "+f"(d[28]), "+f"(d[29]), "+f"(d[30]), "+f"(d[31])
    : "l"(da), "l"(db));
}
__device__ __forceinline__ void wgmma_gemm_n192(float (&d)[96], uint64_t da, uint64_t db) {
  asm volatile("wgmma.mma_async.sync.aligned.m64n192k16.f32.bf16.bf16 "
      "{%0,%1,%2,%3,%4,%5,%6,%7,%8,%9,%10,%11,%12,%13,%14,%15,%16,%17,%18,%19,%20,%21,%22,%23,%24,%25,%26,%27,%28,%29,%30,%31,%32,%33,%34,%35,%36,%37,%38,%39,%40,%41,%42,%43,%44,%45,%46,%47,%48,%49,%50,%51,%52,%53,%54,%55,%56,%57,%58,%59,%60,%61,%62,%63,%64,%65,%66,%67,%68,%69,%70,%71,%72,%73,%74,%75,%76,%77,%78,%79,%80,%81,%82,%83,%84,%85,%86,%87,%88,%89,%90,%91,%92,%93,%94,%95}, "
      "%96, %97, 1, 1, 1, 0, 1;"
    : "+f"(d[0]), "+f"(d[1]), "+f"(d[2]), "+f"(d[3]), "+f"(d[4]), "+f"(d[5]), "+f"(d[6]), "+f"(d[7]), "+f"(d[8]),
      "+f"(d[9]), "+f"(d[10]), "+f"(d[11]), "+f"(d[12]), "+f"(d[13]), "+f"(d[14]), "+f"(d[15]), "+f"(d[16]),
      "+f"(d[17]), "+f"(d[18]), "+f"(d[19]), "+f"(d[20]), "+f"(d[21]), "+f"(d[22]), "+f"(d[23]), "+f"(d[24]),
      "+f"(d[25]), "+f"(d[26]), "+f"(d[27]), "+f"(d[28]), "+f"(d[29]), "+f"(d[30]), "+f"(d[31]), "+f"(d[32]),
      "+f"(d[33]), "+f"(d[34]), "+f"(d[35]), "+f"(d[36]), "+f"(d[37]), "+f"(d[38]), "+f"(d[39]), "+f"(d[40]),
      "+f"(d[41]), "+f"(d[42]), "+f"(d[43]), "+f"(d[44]), "+f"(d[45]), "+f"(d[46]), "+f"(d[47]), "+f"(d[48]),
      "+f"(d[49]), "+f"(d[50]), "+f"(d[51]), "+f"(d[52]), "+f"(d[53]), "+f"(d[54]), "+f"(d[55]), "+f"(d[56]),
      "+f"(d[57]), "+f"(d[58]), "+f"(d[59]), "+f"(d[60]), "+f"(d[61]), "+f"(d[62]), "+f"(d[63]), "+f"(d[64]),
      "+f"(d[65]), "+f"(d[66]), "+f"(d[67]), "+f"(d[68]), "+f"(d[69]), "+f"(d[70]), "+f"(d[71]), "+f"(d[72]),
      "+f"(d[73]), "+f"(d[74]), "+f"(d[75]), "+f"(d[76]), "+f"(d[77]), "+f"(d[78]), "+f"(d[79]), "+f"(d[80]),
      "+f"(d[81]), "+f"(d[82]), "+f"(d[83]), "+f"(d[84]), "+f"(d[85]), "+f"(d[86]), "+f"(d[87]), "+f"(d[88]),
      "+f"(d[89]), "+f"(d[90]), "+f"(d[91]), "+f"(d[92]), "+f"(d[93]), "+f"(d[94]), "+f"(d[95])
    : "l"(da), "l"(db));
}

constexpr float QSCALE = 0.25f * 1.4426950408889634f;
constexpr float LN_EPS = 1e-5f;

__device__ __forceinline__ void row_stats(int layer, int row, float& mu, float& rstd) {
  const float4* p = reinterpret_cast<const float4*>(g_stats + (layer * S_ + row) * 8);
  float4 a = __ldcg(p), b = __ldcg(p + 1), c = __ldcg(p + 2), d = __ldcg(p + 3);
  float s = (a.x + a.z) + (b.x + b.z) + (c.x + c.z) + (d.x + d.z);
  float q = (a.y + a.w) + (b.y + b.w) + (c.y + c.w) + (d.y + d.w);
  mu = s * (1.f / D_);
  float var = fmaxf(q * (1.f / D_) - mu * mu, 0.f);
  rstd = rsqrtf(var + LN_EPS);
}

__global__ void __launch_bounds__(256) prep_kernel(const __nv_bfloat16* __restrict__ x, const __nv_bfloat16* __restrict__ wqkv,
                                                   const __nv_bfloat16* __restrict__ wq, const __nv_bfloat16* __restrict__ wk,
                                                   const __nv_bfloat16* __restrict__ wv) {
  TM(0, 0);
  pdl_launch();
  __shared__ float red[8][16];
  const int b = blockIdx.x, tid = threadIdx.x, lane = tid & 31, warp = tid >> 5;
  {
    const __nv_bfloat16* w; int ld, out;
    if (b < 96) { w = wqkv + b * 16; ld = 1536; out = b * 16; }
    else if (b < 128) { w = wq + (b - 96) * 16; ld = 512; out = 1536 + (b - 96) * 16; }
    else { w = (b == 128) ? wk : wv; ld = 16; out = 2048 + (b - 128) * 16; }
    const int half = tid & 1, r0 = tid >> 1;
    float acc[8];
#pragma unroll
    for (int i = 0; i < 8; i++) acc[i] = 0.f;
#pragma unroll
    for (int j = 0; j < 4; j++) {
      uint4 v = __ldg(reinterpret_cast<const uint4*>(w + (size_t)(r0 + 128 * j) * ld + half * 8));
      if (b >= 128) *reinterpret_cast<uint4*>(g_wkv + (r0 + 128 * j) * 32 + (b - 128) * 16 + half * 8) = v;
      acc[0] += bf_lo(v.x); acc[1] += bf_hi(v.x); acc[2] += bf_lo(v.y); acc[3] += bf_hi(v.y);
      acc[4] += bf_lo(v.z); acc[5] += bf_hi(v.z); acc[6] += bf_lo(v.w); acc[7] += bf_hi(v.w);
    }
#pragma unroll
    for (int i = 0; i < 8; i++) {
#pragma unroll
      for (int o = 2; o < 32; o <<= 1) acc[i] += __shfl_xor_sync(0xffffffffu, acc[i], o);
    }
    if (lane < 2) {
#pragma unroll
      for (int i = 0; i < 8; i++) red[warp][lane * 8 + i] = acc[i];
    }
    __syncthreads();
    if (tid < 16) {
      float s = 0.f;
#pragma unroll
      for (int w8 = 0; w8 < 8; w8++) s += red[w8][tid];
      g_colsum[out + tid] = s;
    }
    if (b == 129 && tid >= 32 && tid < 64) g_colsum[2048 + tid] = 0.f;
  }
  if (b < 128) {
#pragma unroll
    for (int j = 0; j < 2; j++) {
      const int row = b * 16 + warp * 2 + j;
      const uint4* p = reinterpret_cast<const uint4*>(x + (size_t)row * D_ + lane * 16);
      uint4 v0 = __ldg(p), v1 = __ldg(p + 1);
      uint32_t u[8] = {v0.x, v0.y, v0.z, v0.w, v1.x, v1.y, v1.z, v1.w};
      float s = 0.f, q = 0.f;
#pragma unroll
      for (int i = 0; i < 8; i++) {
        float a = bf_lo(u[i]), c = bf_hi(u[i]);
        s += a + c; q = fmaf(a, a, fmaf(c, c, q));
      }
      s += __shfl_xor_sync(0xffffffffu, s, 1); q += __shfl_xor_sync(0xffffffffu, q, 1);
      s += __shfl_xor_sync(0xffffffffu, s, 2); q += __shfl_xor_sync(0xffffffffu, q, 2);
      if ((lane & 3) == 0) g_stats[row * 8 + (lane >> 2)] = make_float2(s, q);
    }
  }
  TM(0, 4);
}

__device__ __forceinline__ int tok0(int r, int rb) { return (rb >> 2) * 512 + r * 256 + (rb & 3) * 64; }
__device__ __forceinline__ int key_pos(int token) {
  const int r = (token >> 8) & 1, rb = ((token >> 9) << 2) | ((token >> 6) & 3), row = token & 63;
  return (16 * r + (row >> 2)) * 64 + rb * 4 + (row & 3);
}
__device__ __forceinline__ float sq_norm16(const uint4& a, const uint4& b) {
  const uint32_t u[8] = {a.x, a.y, a.z, a.w, b.x, b.y, b.z, b.w};
  __half2 n = __hmul2(*reinterpret_cast<const __half2*>(&u[0]), *reinterpret_cast<const __half2*>(&u[0]));
#pragma unroll
  for (int i = 1; i < 8; i++) n = __hfma2(*reinterpret_cast<const __half2*>(&u[i]), *reinterpret_cast<const __half2*>(&u[i]), n);
  return __low2float(n) + __high2float(n);
}
__device__ __forceinline__ uint32_t hsub2(uint32_t a, uint32_t b) {
  uint32_t d; asm("sub.rn.f16x2 %0, %1, %2;" : "=r"(d) : "r"(a), "r"(b)); return d;
}
__device__ __forceinline__ void proj_store(uint32_t a, uint32_t ap, int type, int layer, int head, int token) {
  const uint4 v0 = lds128(a), v1 = lds128(a + 16);
  const size_t hb = (size_t)((layer & 1) * H_ + head) * (S_ * 2);
  if (type == 2) {
    uint4* dst = g_v + hb + key_pos(token);
    dst[0] = v0; dst[S_] = v1;
    return;
  }
  if (type == 0) {
    uint4* dst = g_q + hb + (token >> 3) * 16 + (token & 7);
    dst[0] = v0; dst[8] = v1;
  } else {
    uint4 d0 = v0, d1 = v1;
    if (ap) {
      const uint4 p0 = lds128(ap), p1 = lds128(ap + 16);
      d0 = make_uint4(hsub2(v0.x, p0.x), hsub2(v0.y, p0.y), hsub2(v0.z, p0.z), hsub2(v0.w, p0.w));
      d1 = make_uint4(hsub2(v1.x, p1.x), hsub2(v1.y, p1.y), hsub2(v1.z, p1.z), hsub2(v1.w, p1.w));
    }
    const int pos = key_pos(token);
    uint4* dst = g_k + hb + (pos >> 3) * 16 + (pos & 7);
    dst[0] = d0; dst[8] = d1;
  }
  const unsigned m = __reduce_max_sync(0xffffffffu, __float_as_uint(sq_norm16(v0, v1)) & 0x7fffffffu);
  if ((threadIdx.x & 31) == 0) g_nrm[((layer * 2 + type) * H_ + head) * 64 + (token >> 5)] = __uint_as_float(m);
}
template <int N>
__device__ __forceinline__ void proj_stage(const float (&acc)[N], int j  , uint32_t addr, const float* cs,
                                           int type, float mu0, float rs0, float mu1, float rs1) {
  const float f0 = type == 0 ? rs0 * QSCALE : rs0, f1 = type == 0 ? rs1 * QSCALE : rs1;
  float a[8];
#pragma unroll
  for (int e = 0; e < 2; e++) {
    const float2 c = *reinterpret_cast<const float2*>(cs + (j + e) * 8);
    a[e * 4 + 0] = fmaf(-mu0, c.x, acc[(j + e) * 4 + 0]) * f0; a[e * 4 + 1] = fmaf(-mu0, c.y, acc[(j + e) * 4 + 1]) * f0;
    a[e * 4 + 2] = fmaf(-mu1, c.x, acc[(j + e) * 4 + 2]) * f1; a[e * 4 + 3] = fmaf(-mu1, c.y, acc[(j + e) * 4 + 3]) * f1;
  }
  if (type == 2) stsm4(addr + j * 16, pack_bf16(a[0], a[1]), pack_bf16(a[2], a[3]), pack_bf16(a[4], a[5]), pack_bf16(a[6], a[7]));
  else stsm4(addr + j * 16, pack_f16(a[0], a[1]), pack_f16(a[2], a[3]), pack_f16(a[4], a[5]), pack_f16(a[6], a[7]));
}

constexpr int G1A_NS = 5, G1A_STAGE = 16384 + 3 * 8192, G1A_PITCH = 400;
constexpr int G1A_SMEM = G1A_NS * G1A_STAGE + 1024 + 192 * 4 + 128;
__global__ void __launch_bounds__(288, 1) g1a_kernel(const __grid_constant__ CUtensorMap mx, const __grid_constant__ CUtensorMap mw) {
  extern __shared__ uint8_t smem_raw[];
  const uint32_t sbase = (s2u(smem_raw) + 1023) & ~1023u;
  const uint32_t s_cs = sbase + G1A_NS * G1A_STAGE, s_bar = s_cs + 192 * 4;
  float* cs = reinterpret_cast<float*>(smem_raw + (s_cs - s2u(smem_raw)));
  const int tid = threadIdx.x, warp = tid >> 5, lane = tid & 31;
  const int nb = blockIdx.x & 7, rb = blockIdx.x >> 3;
  TM(1, 0);
  if (tid == 0) {
    for (int i = 0; i < G1A_NS; i++) { mbar_init(s_bar + i * 8, 1); mbar_init(s_bar + 40 + i * 8, 2); }
    fence_bar_init();
  }
  __syncthreads();
  if (warp == 8) {
    if (lane == 0) {
      for (int c = 0; c < 8; c++) {
        const int s = c < G1A_NS ? c : c - G1A_NS;
        const uint32_t st = sbase + s * G1A_STAGE, bar = s_bar + s * 8;
        if (c >= G1A_NS) mbar_wait(s_bar + 40 + s * 8, 0);
        mbar_expect(bar, G1A_STAGE);
        tma_load(st, &mx, c * 64, tok0(0, rb), bar);
        tma_load(st + 8192, &mx, c * 64, tok0(1, rb), bar);
        for (int j = 0; j < 3; j++) tma_load(st + 16384 + j * 8192, &mw, nb * 192 + j * 64, c * 64, bar);
      }
    }
    return;
  }
  const int wg = warp >> 2;
  float acc[96];
#pragma unroll
  for (int i = 0; i < 96; i++) acc[i] = 0.f;
  pin(acc);
#pragma unroll 1
  for (int c = 0; c < 8; c++) {
    const int s = c < G1A_NS ? c : c - G1A_NS;
    mbar_wait(s_bar + s * 8, c >= G1A_NS);
    if (c == 0) TM(1, 2);
    const uint32_t st = sbase + s * G1A_STAGE;
    const uint64_t da = mkdesc(st + wg * 8192, 16, 1024, 1), db = mkdesc(st + 16384, 8192, 1024, 1);
    wg_fence();
#pragma unroll
    for (int k = 0; k < 4; k++) wgmma_gemm_n192(acc, da + k * 2, db + k * 128);
    wg_commit();
    if (c >= 1 && c <= 3) { wg_wait<1>(); if ((tid & 127) == 0) mbar_arrive(s_bar + 40 + (c - 1) * 8); }
    if (c == 5) {
      pdl_wait();
      pdl_launch();
      if (tid < 192) cs[tid] = __ldcg(g_colsum + nb * 192 + tid);
    }
  }
  float mu0, rs0, mu1, rs1;
  const int row0 = tok0(wg, rb) + (warp & 3) * 16 + (lane >> 2);
  row_stats(0, row0, mu0, rs0); row_stats(0, row0 + 8, mu1, rs1);
  wg_wait<0>();
  pin(acc);
  TM(1, 3);
  named_sync(1, 256);
  {
    const uint32_t addr = sbase + (wg * 64 + (warp & 3) * 16 + (lane & 15)) * G1A_PITCH + (lane >> 4) * 16;
#pragma unroll
    for (int j = 0; j < 24; j += 2) proj_stage(acc, j, addr, cs + (lane & 3) * 2, (nb * 12 + (j >> 1)) >> 5, mu0, rs0, mu1, rs1);
  }
  named_sync(1, 256);
#pragma unroll
  for (int it = 0; it < 6; it++) {
    const int item = warp + it * 8, hh = item >> 2, trow = (item & 3) * 32 + lane;
    const int hg = nb * 12 + hh;
    const uint32_t a = sbase + trow * G1A_PITCH + hh * 32;
    proj_store(a, trow >= 4 ? a - 4 * G1A_PITCH : 0u, hg >> 5, 0, hg & 31, tok0(trow >> 6, rb) + (trow & 63));
  }
  TM(1, 4);
}

constexpr uint32_t MUFU_MASK = 0xF800u;
constexpr float EXP_MAGIC = 383.0f + 0.65f / 128.0f;
constexpr uint32_t POLY_A = 0x5a835a83u, POLY_B = 0x92a192a1u, POLY_C = 0x800b800bu;
constexpr float SCORE_LIMIT = 116.f;

__device__ __forceinline__ void exp_step(const float (&s)[32], uint32_t (&p)[16], uint32_t pb) {
#pragma unroll
  for (int i = 0; i < 16; i++) {
    if ((MUFU_MASK >> i) & 1) {
      float a, b;
      asm("ex2.approx.ftz.f32 %0, %1;" : "=f"(a) : "f"(s[2 * i]));
      asm("ex2.approx.ftz.f32 %0, %1;" : "=f"(b) : "f"(s[2 * i + 1]));
      p[i] = pack_bf16(a, b);
    } else {
      uint32_t z, u, h;
      asm("prmt.b32 %0, %1, %2, 0x6521;" : "=r"(z) : "r"(__float_as_uint(s[2 * i])), "r"(__float_as_uint(s[2 * i + 1])));
      asm("fma.rn.f16x2 %0, %1, %2, %3;" : "=r"(u) : "r"(z & 0x007f007fu), "r"(POLY_A), "r"(pb));
      asm("fma.rn.f16x2 %0, %1, %1, %2;" : "=r"(h) : "r"(u), "r"(POLY_C));
      p[i] = z - h;
    }
  }
}

template <bool PV>
__device__ __forceinline__ void att_step(float (&s)[32], float (&o)[12], uint32_t (&pin_)[16], uint32_t (&pout)[16], uint64_t dq,
                                         uint64_t dk, uint64_t dv, uint32_t pb) {
  pin(s);
  if (PV) pin(pin_);
  wg_fence();
  wgmma_qk_n64(s, dq, dk);
  wg_commit();
  if (PV) {
#pragma unroll
    for (int j = 0; j < 4; j++) wgmma_pv_n24(o, pin_[4 * j], pin_[4 * j + 1], pin_[4 * j + 2], pin_[4 * j + 3], dv + j * 16);
    wg_commit();
    wg_wait<1>();
  } else {
    wg_wait<0>();
  }
  pin(s);
  exp_step(s, pout, pb);
  pin(pout);
}

constexpr int M_STAGE = 0;
constexpr int M_STG = 65536, STG_PITCH = 144;
constexpr int M_KV = 74752;
constexpr int M_Q = M_KV + 17 * 8192;
constexpr int M_CS = M_Q + 16384, M_KTAIL = M_CS + 256, M_ROW = M_KTAIL + 512, M_BAR = M_ROW + 512;
constexpr int MEGA_SMEM = M_BAR + 128;
__device__ __forceinline__ int k_unit(int j) { return j < 2 ? 7 + 2 * j : j - 2; }
__device__ __forceinline__ int v0_unit(int b) { return b == 0 ? 14 : 12 - 2 * b; }
__device__ __forceinline__ int v_stride(int b) { return b == 0 ? 1 : b + 2; }
constexpr int B_FULL = 0, B_EMPTY = 32, B_KV = 64, B_Q = 80, B_FREE0 = 96, B_ODONE = 104, B_RES = 120;

struct MegaParams {
  CUtensorMap m[8];
  const __nv_bfloat16* x0;
  const __nv_bfloat16* wqkv; const __nv_bfloat16* wq; const __nv_bfloat16* wk;
  __nv_bfloat16* out;
};

__device__ __forceinline__ void cnt_signal(int idx) {
  if (elect_one()) asm volatile("red.release.gpu.global.add.u32 [%0], 1;" ::"l"(g_cnt + idx) : "memory");
}
__device__ __forceinline__ void cnt_wait(int idx, unsigned target) {
  unsigned v;
  int it = 0;
  while (true) {
    asm volatile("ld.acquire.gpu.global.u32 %0, [%1];" : "=r"(v) : "l"(g_cnt + idx) : "memory");
    if (v >= target) break;
    if (++it > (1 << 24)) __trap();
    __nanosleep(32);
  }
  asm volatile("fence.proxy.async.global;" ::: "memory");
}

__device__ __forceinline__ void att_fallback(const MegaParams& P, int layer, int head, int row0, __nv_bfloat16* sk, int bar_id) {
  const int t = threadIdx.x & 127, hf = t & 1;
  const __nv_bfloat16* x = layer == 0 ? P.x0 : g_x + (size_t)(layer - 1) * S_ * D_;
  const bool mqa = layer & 1;
  const __nv_bfloat16* vimg = reinterpret_cast<const __nv_bfloat16*>(g_v + (size_t)((layer & 1) * H_ + (mqa ? 0 : head)) * (S_ * 2));
  float q[16], o[16], acc[16];
  float m = -INFINITY, l = 0.f;
#pragma unroll
  for (int d = 0; d < 16; d++) { o[d] = 0.f; q[d] = 0.f; }
#pragma unroll 1
  for (int ch = -1; ch < 32; ch++) {
    const int token = ch < 0 ? row0 + (t >> 1) : ch * 64 + (t >> 1);
    const __nv_bfloat16* w = ch < 0 ? (mqa ? P.wq : P.wqkv) + head * 16 : (mqa ? P.wk : P.wqkv + 512 + head * 16);
    const int ld = mqa ? (ch < 0 ? 512 : 16) : 1536;
    float mu, rs;
    row_stats(layer, token, mu, rs);
#pragma unroll
    for (int d = 0; d < 16; d++) acc[d] = 0.f;
#pragma unroll 1
    for (int k = hf * 256; k < hf * 256 + 256; k++) {
      const unsigned short xr = __ldcg(reinterpret_cast<const unsigned short*>(x) + (size_t)token * D_ + k);
      const float xn = __bfloat162float(__float2bfloat16((__uint_as_float((uint32_t)xr << 16) - mu) * rs));
#pragma unroll
      for (int d = 0; d < 16; d++) acc[d] = fmaf(xn, __bfloat162float(w[(size_t)k * ld + d]), acc[d]);
    }
#pragma unroll
    for (int d = 0; d < 16; d++) acc[d] = __bfloat162float(__float2bfloat16(acc[d] + __shfl_xor_sync(0xffffffffu, acc[d], 1)));
    if (ch < 0) {
#pragma unroll
      for (int d = 0; d < 16; d++) q[d] = acc[d];
      continue;
    }
    named_sync(bar_id, 128);
    if (hf == 0) {
#pragma unroll
      for (int d = 0; d < 16; d++) sk[(t >> 1) * 16 + d] = __float2bfloat16(acc[d]);
    }
    named_sync(bar_id, 128);
#pragma unroll 1
    for (int j = hf * 32; j < hf * 32 + 32; j++) {
      float sc = 0.f;
#pragma unroll
      for (int d = 0; d < 16; d++) sc = fmaf(q[d], __bfloat162float(sk[j * 16 + d]), sc);
      sc *= 0.25f;
      if (sc > m || sc != sc) {
        const float a = __expf(m - sc);
        l *= a;
#pragma unroll
        for (int d = 0; d < 16; d++) o[d] *= a;
        m = sc;
      }
      const float p = __expf(sc - m);
      l += p;
      const int pos = key_pos(ch * 64 + j);
#pragma unroll
      for (int d = 0; d < 16; d++) {
        const unsigned short vr = __ldcg(reinterpret_cast<const unsigned short*>(vimg) + (d >> 3) * (S_ * 8) + pos * 8 + (d & 7));
        o[d] = fmaf(p, __uint_as_float((uint32_t)vr << 16), o[d]);
      }
    }
  }
  const float m2 = __shfl_xor_sync(0xffffffffu, m, 1), mm = fmaxf(m, m2), a = __expf(m - mm);
  l *= a; l += __shfl_xor_sync(0xffffffffu, l, 1);
  const float inv = 1.f / l;
  __nv_bfloat16* dst = g_o + (size_t)(row0 + (t >> 1)) * D_ + head * 16;
#pragma unroll
  for (int d = 0; d < 16; d++) {
    float v = o[d] * a; v += __shfl_xor_sync(0xffffffffu, v, 1);
    if ((d >> 3) == hf) dst[d] = __float2bfloat16(v * inv);
  }
}

__device__ __forceinline__ void issue_b(const MegaParams& P, uint32_t sbase, int code, int c) {
  const int l = code >> 3, p = code & 3, ct = blockIdx.x & 7;
  const CUtensorMap* m = &P.m[p == 0 ? 5 + (l & 1) : ((l & 1) ? 2 : (p == 3 ? 3 : 4))];
  const int col = p == 0 || p == 3 ? ct * 64 : ((l & 1) ? p * 512 + ct * 64 : 0);
  const uint32_t bar = sbase + M_BAR + B_FULL + (c & 3) * 8;
  if (elect_one()) {
    mbar_expect(bar, 16384);
    tma_load(sbase + M_STAGE + (c & 3) * 16384 + 8192, m, col, c * 64, bar);
  }
}
__device__ __forceinline__ void issue_a(const MegaParams& P, uint32_t sbase, int code, int c) {
  const bool o = (code & 3) == 0;
  const int row = tok0((code >> 2) & 1, blockIdx.x >> 3) + (o ? 0 : (code >> 3) * S_);
  if (elect_one()) tma_load(sbase + M_STAGE + (c & 3) * 16384, &P.m[o ? 1 : 0], c * 64, row, sbase + M_BAR + B_FULL + (c & 3) * 8);
}
__device__ __forceinline__ void refill(const MegaParams& P, uint32_t sbase, int w4, int c, int code, int next) {
  const uint32_t eb = sbase + M_BAR + B_EMPTY + ((c - 1) & 3) * 8;
  if (elect_one()) mbar_arrive(eb);
  if (w4 == 0 && (c < 5 || next < 32)) {
    mbar_wait(eb, ((c - 1) >> 2) & 1);
    const int cd = c < 5 ? code : next, cc = c < 5 ? c + 3 : c - 5;
    issue_b(P, sbase, cd, cc);
    if (c < 5 || ((code & 3) != 0 && (next & 3) != 0)) issue_a(P, sbase, cd, cc);
  }
}
__device__ __forceinline__ void load_kv(uint32_t sbase, int l, int r) {
  const size_t hb = (size_t)((l & 1) * H_ + ((l & 1) ? 0 : blockIdx.x >> 2)) * 65536;
  const uint8_t* gk = reinterpret_cast<const uint8_t*>(g_k) + hb;
  const uint8_t* gv = reinterpret_cast<const uint8_t*>(g_v) + hb;
  const uint32_t bar = sbase + M_BAR + B_KV + r * 8;
  if (elect_one()) {
    mbar_expect(bar, 65536);
#pragma unroll
    for (int j = 0; j < 2; j++) {
      const int b = r * 2 + j;
      bulk_load(sbase + M_KV + k_unit(2 * b) * 8192, gk + b * 16384, 8192, bar);
      bulk_load(sbase + M_KV + v0_unit(b) * 8192, gv + b * 8192, 8192, bar);
      bulk_load(sbase + M_KV + (v0_unit(b) + v_stride(b)) * 8192, gv + 32768 + b * 8192, 8192, bar);
      bulk_load(sbase + M_KV + k_unit(2 * b + 1) * 8192, gk + b * 16384 + 8192, 8192, bar);
    }
  }
}
__device__ __forceinline__ void load_q(uint32_t sbase, int l, int r) {
  const uint32_t bar = sbase + M_BAR + B_Q + r * 8;
  if (elect_one()) {
    mbar_expect(bar, 8192);
    bulk_load(sbase + M_Q + r * 8192,
              reinterpret_cast<const uint8_t*>(g_q) + (size_t)((l & 1) * H_ + (blockIdx.x >> 2)) * 65536 + (blockIdx.x & 3) * 16384 + r * 8192,
              8192, bar);
  }
}

__global__ void __launch_bounds__(640, 1) mega_kernel(const __grid_constant__ MegaParams P) {
  extern __shared__ __align__(1024) uint8_t sm[];
  const uint32_t sbase = s2u(sm);
  if (sbase & 1023) __trap();
  const uint32_t s_bar = sbase + M_BAR;
  const int tid = threadIdx.x, warp = tid >> 5, lane = tid & 31;
  const int head = blockIdx.x >> 2, quarter = blockIdx.x & 3;
  TM(2, 0);
  if (tid == 0) {
    for (int i = 0; i < 4; i++) { mbar_init(s_bar + B_FULL + i * 8, 1); mbar_init(s_bar + B_EMPTY + i * 8, 4); }
    for (int i = 0; i < 2; i++) { mbar_init(s_bar + B_KV + i * 8, 1); mbar_init(s_bar + B_Q + i * 8, 1); mbar_init(s_bar + B_ODONE + i * 8, 16); }
    mbar_init(s_bar + B_FREE0, 16);
    mbar_init(s_bar + B_RES, 1);
    fence_bar_init();
  }
  if (tid < 512) *reinterpret_cast<uint4*>(sm + M_KV + 16 * 8192 + tid * 16) = make_uint4(0x3f803f80u, 0x3f803f80u, 0x3f803f80u, 0x3f803f80u);
  fence_async_smem();
  __syncthreads();
  const int wg = __shfl_sync(0xffffffffu, warp >> 2, 0);

  if (wg < 4) {
    asm volatile("setmaxnreg.inc.sync.aligned.u32 104;");
    pdl_wait();
    uint32_t pb = POLY_B;
    asm volatile("" : "+r"(pb));
#pragma unroll 1
    for (int lr = 0; lr < 8; lr++) {
      const int rnd = lr & 1, layer = lr >> 1;
      const uint32_t par = layer & 1;
      float s[32], o[12];
      uint32_t p0[16], p1[16];
#pragma unroll
      for (int i = 0; i < 32; i++) s[i] = ((MUFU_MASK >> (i >> 1)) & 1) ? 0.f : EXP_MAGIC;
#pragma unroll
      for (int i = 0; i < 12; i++) o[i] = 0.f;
      const uint64_t dq = mkdesc(sbase + M_Q + rnd * 8192 + wg * 2048, 128, 256, 0);
      uint64_t dvp = mkdesc(sbase + M_KV + 14 * 8192, 128, 8192, 0);
      pin(o);
      mbar_wait(s_bar + B_Q + rnd * 8, par);
      mbar_wait(s_bar + B_KV, par);
      TM(3 + lr, 0);
      {
        const uint64_t dk = mkdesc(sbase + M_KV + 7 * 8192, 128, 256, 0);
        att_step<false>(s, o, p1, p0, dq, dk, dvp, pb);
        att_step<true>(s, o, p0, p1, dq, dk + 128, dvp, pb);
        att_step<true>(s, o, p1, p0, dq, dk + 256, dvp + 64, pb);
        att_step<true>(s, o, p0, p1, dq, dk + 384, dvp + 128, pb);
        att_step<true>(s, o, p1, p0, dq, dk + 1024, dvp + 192, pb);
        att_step<true>(s, o, p0, p1, dq, dk + 1024 + 128, dvp + 256, pb);
        att_step<true>(s, o, p1, p0, dq, dk + 1024 + 256, dvp + 320, pb);
        att_step<true>(s, o, p0, p1, dq, dk + 1024 + 384, dvp + 384, pb);
        wg_wait<0>();
      }
      uint64_t dk = mkdesc(sbase + M_KV, 128, 256, 0), dv = mkdesc(sbase + M_KV + 10 * 8192, 128, 3 * 8192, 0);
#pragma unroll 1
      for (int b = 1; b < 4; b++) {
        if (b == 2) { TM(3 + lr, 1); mbar_wait(s_bar + B_KV + 8, par); TM(3 + lr, 2); }
        att_step<true>(s, o, p1, p0, dq, dk, dvp + 448, pb);
        att_step<true>(s, o, p0, p1, dq, dk + 128, dv, pb);
#pragma unroll
        for (int u = 2; u < 8; u += 2) {
          att_step<true>(s, o, p1, p0, dq, dk + u * 128, dv + (u - 1) * 64, pb);
          att_step<true>(s, o, p0, p1, dq, dk + (u + 1) * 128, dv + u * 64, pb);
        }
        wg_wait<0>();
        if (b == 2 && rnd == 1 && lane == 0) mbar_arrive(s_bar + B_FREE0);
        dvp = dv;
        dk += 1024;
        dv += (512ull << 32) - 1024ull;
      }
      pin(p1);
      wg_fence();
#pragma unroll
      for (int j = 0; j < 4; j++) wgmma_pv_n24(o, p1[4 * j], p1[4 * j + 1], p1[4 * j + 2], p1[4 * j + 3], dvp + 448 + j * 16);
      wg_commit();
      const int row0 = quarter * 512 + rnd * 256 + wg * 64;
      const float* nq = g_nrm + (layer * 2 * H_ + head) * 64 + (row0 >> 5);
      const float* nk = g_nrm + ((layer * 2 + 1) * H_ + (par ? 0 : head)) * 64;
      const unsigned qn = max(__float_as_uint(__ldcg(nq)), __float_as_uint(__ldcg(nq + 1)));
      const unsigned kn = __reduce_max_sync(0xffffffffu, max(__float_as_uint(__ldcg(nk + lane)), __float_as_uint(__ldcg(nk + 32 + lane))));
      wg_wait<0>();
      pin(o);
      const float l0 = o[8], l1 = o[10];
      float mx = 0.f;
#pragma unroll
      for (int i = 0; i < 8; i++) mx += fabsf(o[i]);
      const bool ok = __uint_as_float(qn) * __uint_as_float(kn) <= SCORE_LIMIT * SCORE_LIMIT && l0 >= 1e-18f && l0 <= 1e37f &&
                      l1 >= 1e-18f && l1 <= 1e37f && mx <= 3e38f;
      uint32_t bad;
      asm volatile("{.reg .pred p, q; setp.eq.u32 p, %1, 0; barrier.red.or.pred.aligned q, %2, 128, p; selp.u32 %0, 1, 0, q;}"
                   : "=r"(bad) : "r"((uint32_t)ok), "r"(wg + 1) : "memory");
      if (bad) {
        att_fallback(P, layer, head, row0, reinterpret_cast<__nv_bfloat16*>(sm + M_Q + rnd * 8192 + wg * 2048), wg + 1);
        fence_async_smem();
      } else {
        const float i0 = __fdividef(1.f, l0), i1 = __fdividef(1.f, l1);
        __nv_bfloat16* dst = g_o + (size_t)(row0 + (warp & 3) * 16 + (lane >> 2)) * D_ + head * 16 + (lane & 3) * 2;
        *reinterpret_cast<uint32_t*>(dst) = pack_bf16(o[0] * i0, o[1] * i0);
        *reinterpret_cast<uint32_t*>(dst + 8) = pack_bf16(o[4] * i0, o[5] * i0);
        *reinterpret_cast<uint32_t*>(dst + 8 * D_) = pack_bf16(o[2] * i1, o[3] * i1);
        *reinterpret_cast<uint32_t*>(dst + 8 * D_ + 8) = pack_bf16(o[6] * i1, o[7] * i1);
      }
      __syncwarp();
      if (lane == 0) mbar_arrive(s_bar + B_ODONE + rnd * 8);
      TM(3 + lr, 3);
    }
  } else {
    asm volatile("setmaxnreg.dec.sync.aligned.u32 64;");
    const int t = tid - 512, w4 = __shfl_sync(0xffffffffu, warp & 3, 0);
    if (w4 == 0) {
#pragma unroll
      for (int c = 0; c < 4; c++) issue_b(P, sbase, 0, c);
    }
    pdl_wait();
    if (w4 == 0) { load_q(sbase, 0, 0); load_kv(sbase, 0, 0); }
    if (w4 == 1) { load_kv(sbase, 0, 1); load_q(sbase, 0, 1); }
    int code = 0;
#pragma unroll 1
    while (true) {
      code = __shfl_sync(0xffffffffu, code, 0);
      int next;
      {
        const int p = code & 3, l = code >> 3;
        const int np = l == 3 ? 4 : ((l & 1) ? p + 1 : (p == 0 && (blockIdx.x & 7) == 0 ? 1 : (p < 3 ? 3 : 4)));
        next = (code & ~3) + np;
      }
      if ((code & 3) == 0) {
        if (w4 == 0) {
          const int lr = code >> 2;
          if (elect_one()) {
            asm volatile("fence.proxy.async;" ::: "memory");
            mbar_expect(s_bar + B_RES, 8192);
            tma_load(sbase + M_STG, &P.m[lr < 2 ? 7 : 0], (blockIdx.x & 7) * 64,
                     tok0(lr & 1, blockIdx.x >> 3) + (lr < 2 ? 0 : ((lr >> 1) - 1) * S_), s_bar + B_RES);
          }
          mbar_wait(s_bar + B_ODONE + (lr & 1) * 8, (lr >> 1) & 1);
          cnt_signal(CNT_O + lr * 4 + (blockIdx.x & 3));
          TM2(12 + lr, 0);
          cnt_wait(CNT_O + lr * 4 + (blockIdx.x >> 5), 32);
          TM2(12 + lr, 1);
#pragma unroll
          for (int c = 0; c < 4; c++) issue_a(P, sbase, code, c);
        }
      } else {
        const int l = code >> 3, p = code & 3, ct = blockIdx.x & 7;
        if (p == (((l & 1) || ct == 0) ? 1 : 3)) {
          if (w4 == 0) {
            cnt_wait(CNT_X + (code >> 2) * 16 + (blockIdx.x >> 3), 8);
            TM2(12 + (code >> 2), 3);
#pragma unroll
            for (int c = 0; c < 4; c++) issue_a(P, sbase, code, c);
          }
          named_sync(5, 128);
          if (t >= 64) {
            float mu, rs;
            row_stats(l + 1, tok0((code >> 2) & 1, blockIdx.x >> 3) + t - 64, mu, rs);
            reinterpret_cast<float2*>(sm + M_ROW)[t - 64] = make_float2(mu, rs);
          }
        }
        if (t < 64)
          reinterpret_cast<float*>(sm + M_CS)[t] =
              __ldcg(g_colsum + ((l & 1) ? (p == 3 ? 0 : p * 512) + ct * 64 : (p == 3 ? 1536 + ct * 64 : 2048)) + t);
      }
      float acc[32];
#pragma unroll
      for (int i = 0; i < 32; i++) acc[i] = 0.f;
      pin(acc);
#pragma unroll 1
      for (int c = 0; c < 8; c++) {
        const uint32_t st = sbase + M_STAGE + (c & 3) * 16384;
        mbar_wait(s_bar + B_FULL + (c & 3) * 8, c >> 2);
        const uint64_t da = mkdesc(st, 16, 1024, 1), db = mkdesc(st + 8192, 8192, 1024, 1);
        wg_fence();
#pragma unroll
        for (int k = 0; k < 4; k++) wgmma_gemm_n64(acc, da + k * 2, db + k * 128);
        wg_commit();
        wg_wait<1>();
        if (c >= 1) refill(P, sbase, w4, c, code, next);
      }
      wg_wait<0>();
      pin(acc);
      refill(P, sbase, w4, 8, code, next);
      int t;
      asm volatile("mov.u32 %0, %%tid.x;" : "=r"(t));
      t -= 512;
      const int lane = t & 31;
      const int l = code >> 3, r = (code >> 2) & 1, p = code & 3, lr = code >> 2;
      const int rb = blockIdx.x >> 3, ct = blockIdx.x & 7, row0 = tok0(r, rb);
      const uint32_t stg = sbase + M_STG;
      const uint32_t saddr = stg + (w4 * 16 + (lane & 15)) * STG_PITCH + (lane >> 4) * 16;
      if (p == 0) {
        mbar_wait(s_bar + B_RES, lr & 1);
        const uint32_t ra = stg + (w4 * 16 + (lane & 15)) * 128;
        float s0 = 0.f, q0 = 0.f, s1 = 0.f, q1 = 0.f;
#pragma unroll
        for (int j = 0; j < 8; j += 2) {
          const uint32_t a = ra + (((j + (lane >> 4)) ^ (lane & 7)) << 4);
          uint32_t y[4];
          ldsm4(a, y[0], y[1], y[2], y[3]);
#pragma unroll
          for (int e = 0; e < 4; e++) {
            y[e] = hadd2_bf16(y[e], pack_bf16(acc[4 * j + 2 * e], acc[4 * j + 2 * e + 1]));
            const float lo = bf_lo(y[e]), hi = bf_hi(y[e]);
            if (e & 1) { s1 += lo + hi; q1 = fmaf(lo, lo, fmaf(hi, hi, q1)); }
            else { s0 += lo + hi; q0 = fmaf(lo, lo, fmaf(hi, hi, q0)); }
          }
          stsm4(a, y[0], y[1], y[2], y[3]);
        }
        __syncwarp();
        __nv_bfloat16* xout = (l == 3 ? P.out : g_x + (size_t)l * S_ * D_) + (size_t)(row0 + w4 * 16 + (lane >> 3)) * D_ + ct * 64 + (lane & 7) * 8;
#pragma unroll
        for (int i = 0; i < 4; i++) {
          const int rr = i * 4 + (lane >> 3);
          *reinterpret_cast<uint4*>(xout + (size_t)i * 4 * D_) = lds128(stg + (w4 * 16 + rr) * 128 + (((lane & 7) ^ (rr & 7)) << 4));
        }
        if (l < 3) {
#pragma unroll
          for (int o = 1; o < 4; o <<= 1) {
            s0 += __shfl_xor_sync(0xffffffffu, s0, o); q0 += __shfl_xor_sync(0xffffffffu, q0, o);
            s1 += __shfl_xor_sync(0xffffffffu, s1, o); q1 += __shfl_xor_sync(0xffffffffu, q1, o);
          }
          if ((lane & 3) == 0) {
            float2* st = g_stats + ((l + 1) * S_ + row0 + w4 * 16 + (lane >> 2)) * 8 + ct;
            st[0] = make_float2(s0, q0); st[64] = make_float2(s1, q1);
          }
        }
        named_sync(5, 128);
        if (w4 == 0 && l < 3) cnt_signal(CNT_X + lr * 16 + rb);
        TM2(12 + lr, 2);
      } else {
        const bool kv = !(l & 1) && p == 1;
        const int type = p == 3 ? 0 : p;
        named_sync(5, 128);
        const float2 st0 = reinterpret_cast<const float2*>(sm + M_ROW)[w4 * 16 + (lane >> 2)];
        const float2 st1 = reinterpret_cast<const float2*>(sm + M_ROW)[w4 * 16 + (lane >> 2) + 8];
#pragma unroll
        for (int j = 0; j < 8; j += 2)
          proj_stage(acc, j, saddr, reinterpret_cast<const float*>(sm + M_CS) + (lane & 3) * 2, kv ? (j == 0 ? 1 : 2) : type, st0.x, st0.y, st1.x, st1.y);
        named_sync(5, 128);
        const int row = t & 63;
#pragma unroll 1
        for (int i = 0; i < (kv ? 1 : 2); i++) {
          const int hh = 2 * i + (t >> 6);
          const uint32_t a = stg + row * STG_PITCH + hh * 32;
          const uint32_t ap = row >= 4 ? a - 4 * STG_PITCH : (r ? sbase + M_KTAIL + row * 128 + hh * 32 : 0u);
          proj_store(a, ap, kv ? 1 + hh : type, l + 1, kv ? 0 : ct * 4 + hh, row0 + row);
        }
        if (p == 1 && r == 0 && t < 32)
          *reinterpret_cast<uint4*>(sm + M_KTAIL + t * 16) = lds128(stg + (60 + (t >> 3)) * STG_PITCH + (t & 7) * 16);
        named_sync(5, 128);
        if (w4 == 0) {
          if (p == 3) cnt_signal(CNT_Q + (lr * 4 + (rb >> 2)) * 8 + ct);
          else if (kv || p == 2) cnt_signal(CNT_KV + lr * 8 + ct);
        }
      }
      if ((next & 3) == 0) {
        TM2(12 + lr, 4);
        if (next == 32) break;
        if (l < 3 && w4 == 0) {
          if (r == 0) mbar_wait(s_bar + B_FREE0, l & 1);
          cnt_wait(CNT_KV + lr * 8 + ((l & 1) ? blockIdx.x >> 4 : 0), 16);
          load_kv(sbase, l + 1, r);
          cnt_wait(CNT_Q + (lr * 4 + (blockIdx.x & 3)) * 8 + (blockIdx.x >> 4), 4);
          load_q(sbase, l + 1, r);
          TM2(12 + lr, 5);
        }
      }
      code = next;
    }
    if (t == 0) {
      unsigned old;
      asm volatile("atom.acq_rel.gpu.global.add.u32 %0, [%1], 1;" : "=r"(old) : "l"(g_cnt + CNT_DONE) : "memory");
      if (old == gridDim.x - 1)
        for (int i = 0; i < CNT_N; i++) g_cnt[i] = 0u;
    }
  }
}

typedef CUresult (*EncodeFn)(CUtensorMap*, CUtensorMapDataType, cuuint32_t, void*, const cuuint64_t*, const cuuint64_t*,
                             const cuuint32_t*, const cuuint32_t*, CUtensorMapInterleave, CUtensorMapSwizzle,
                             CUtensorMapL2promotion, CUtensorMapFloatOOBfill);

void make_map(EncodeFn enc, CUtensorMap* m, const void* p, int rows, int cols) {
  cuuint64_t dim[2] = {(cuuint64_t)cols, (cuuint64_t)rows};
  cuuint64_t str[1] = {(cuuint64_t)cols * 2};
  cuuint32_t box[2] = {64, 64};
  cuuint32_t es[2] = {1, 1};
  enc(m, CU_TENSOR_MAP_DATA_TYPE_BFLOAT16, 2, const_cast<void*>(p), dim, str, box, es, CU_TENSOR_MAP_INTERLEAVE_NONE,
      CU_TENSOR_MAP_SWIZZLE_128B, CU_TENSOR_MAP_L2_PROMOTION_L2_128B, CU_TENSOR_MAP_FLOAT_OOB_FILL_NONE);
}

template <typename... KA, typename... A>
void launch(void (*k)(KA...), int grid, int block, int smem, bool pdl, A... args) {
  cudaLaunchConfig_t cfg = {};
  cfg.gridDim = dim3(grid); cfg.blockDim = dim3(block); cfg.dynamicSmemBytes = smem; cfg.stream = cudaStreamPerThread;
  cudaLaunchAttribute at[1];
  at[0].id = cudaLaunchAttributeProgrammaticStreamSerialization;
  at[0].val.programmaticStreamSerializationAllowed = 1;
  cfg.attrs = at; cfg.numAttrs = pdl ? 1 : 0;
  cudaLaunchKernelEx(&cfg, k, KA(args)...);
}

struct HostState {
  bool init;
  const void* in[8];
  MegaParams mp;
};
HostState hs;

}

extern "C" void kernel_launch(void* const* d_in, const int* in_sizes, int n_in, void* d_out, int out_size) {
  const __nv_bfloat16* A_x = (const __nv_bfloat16*)d_in[0];
  const __nv_bfloat16* A_wqkv = (const __nv_bfloat16*)d_in[1];
  const __nv_bfloat16* A_wo = (const __nv_bfloat16*)d_in[2];
  const __nv_bfloat16* B_wq = (const __nv_bfloat16*)d_in[4];
  const __nv_bfloat16* B_wk = (const __nv_bfloat16*)d_in[5];
  const __nv_bfloat16* B_wv = (const __nv_bfloat16*)d_in[6];
  const __nv_bfloat16* B_wo = (const __nv_bfloat16*)d_in[7];
  bool same = hs.init;
  for (int i = 0; i < 8; i++) same = same && hs.in[i] == d_in[i];
  if (!same) {
    void* fn = nullptr;
    cudaDriverEntryPointQueryResult qr;
    cudaGetDriverEntryPoint("cuTensorMapEncodeTiled", &fn, cudaEnableDefault, &qr);
    EncodeFn enc = (EncodeFn)fn;
    void *px, *po, *pw;
    cudaGetSymbolAddress(&px, g_x);
    cudaGetSymbolAddress(&po, g_o);
    cudaGetSymbolAddress(&pw, g_wkv);
    make_map(enc, &hs.mp.m[7], A_x, S_, D_);
    make_map(enc, &hs.mp.m[0], px, 3 * S_, D_);
    make_map(enc, &hs.mp.m[1], po, S_, D_);
    make_map(enc, &hs.mp.m[2], A_wqkv, D_, 1536);
    make_map(enc, &hs.mp.m[3], B_wq, D_, 512);
    make_map(enc, &hs.mp.m[4], pw, D_, 32);
    make_map(enc, &hs.mp.m[5], A_wo, D_, D_);
    make_map(enc, &hs.mp.m[6], B_wo, D_, D_);
    hs.mp.x0 = A_x; hs.mp.wqkv = A_wqkv; hs.mp.wq = B_wq; hs.mp.wk = B_wk;
    cudaFuncSetAttribute(prep_kernel, cudaFuncAttributePreferredSharedMemoryCarveout, 100);
    cudaFuncSetAttribute(g1a_kernel, cudaFuncAttributeMaxDynamicSharedMemorySize, G1A_SMEM);
    cudaFuncSetAttribute(mega_kernel, cudaFuncAttributeMaxDynamicSharedMemorySize, MEGA_SMEM);
    for (int i = 0; i < 8; i++) hs.in[i] = d_in[i];
    hs.init = true;
  }
  hs.mp.out = (__nv_bfloat16*)d_out;
  launch(prep_kernel, 130, 256, 0, false, A_x, A_wqkv, B_wq, B_wk, B_wv);
  launch(g1a_kernel, 128, 288, G1A_SMEM, true, hs.mp.m[7], hs.mp.m[2]);
  launch(mega_kernel, 128, 640, MEGA_SMEM, true, hs.mp);
}
```

```cpp
#include <cuda_runtime.h>
#include <cuda_bf16.h>
#include <cuda_fp16.h>
#include <cuda.h>
#include <stdint.h>

namespace {

constexpr int S_ = 2048, D_ = 512, H_ = 32;

__device__ __align__(1024) __nv_bfloat16 g_x[3 * S_ * D_];
__device__ __align__(1024) __nv_bfloat16 g_o[S_ * D_];
__device__ __align__(1024) uint4 g_q[2 * H_ * S_ * 2];
__device__ __align__(1024) uint4 g_k[2 * H_ * S_ * 2];
__device__ __align__(1024) uint4 g_v[2 * H_ * S_ * 2];
__device__ __align__(1024) __nv_bfloat16 g_wkv[D_ * 32];
__device__ __align__(16) float2 g_stats[4 * S_ * 8];
__device__ __align__(16) float g_colsum[1536 + 512 + 64];
__device__ float g_nrm[4 * 2 * H_ * 64];
constexpr int CNT_O = 0, CNT_X = 32, CNT_KV = CNT_X + 128, CNT_Q = CNT_KV + 64, CNT_DONE = CNT_Q + 256, CNT_N = CNT_DONE + 1;
__device__ unsigned g_cnt[CNT_N];

#define TM(k, slot)
#define TM1(k, slot)
#define TM2(k, slot)
#define TM3(k, slot)
__device__ __forceinline__ uint32_t s2u(const void* p) { return (uint32_t)__cvta_generic_to_shared(p); }
__device__ __forceinline__ void mbar_init(uint32_t bar, int cnt) {
  asm volatile("mbarrier.init.shared::cta.b64 [%0], %1;" ::"r"(bar), "r"(cnt) : "memory");
}
__device__ __forceinline__ void mbar_expect(uint32_t bar, uint32_t bytes) {
  asm volatile("mbarrier.arrive.expect_tx.shared::cta.b64 _, [%0], %1;" ::"r"(bar), "r"(bytes) : "memory");
}
__device__ __forceinline__ void mbar_arrive(uint32_t bar) {
  asm volatile("mbarrier.arrive.shared::cta.b64 _, [%0];" ::"r"(bar) : "memory");
}
__device__ __forceinline__ void mbar_wait(uint32_t bar, uint32_t par) {
  uint32_t ok;
  int it = 0;
  do {
    asm volatile("{.reg .pred p; mbarrier.try_wait.parity.shared::cta.b64 p, [%1], %2; selp.u32 %0,1,0,p;}"
                 : "=r"(ok) : "r"(bar), "r"(par) : "memory");
    if (++it > (1 << 24)) __trap();
  } while (!ok);
}
__device__ __forceinline__ void bulk_load(uint32_t dst, const void* src, uint32_t bytes, uint32_t bar) {
  asm volatile("cp.async.bulk.shared::cluster.global.mbarrier::complete_tx::bytes [%0], [%1], %2, [%3];"
               ::"r"(dst), "l"(src), "r"(bytes), "r"(bar) : "memory");
}
__device__ __forceinline__ void tma_load(uint32_t dst, const CUtensorMap* m, int c0, int c1, uint32_t bar) {
  asm volatile("cp.async.bulk.tensor.2d.shared::cluster.global.mbarrier::complete_tx::bytes [%0], [%1, {%3, %4}], [%2];"
               ::"r"(dst), "l"(m), "r"(bar), "r"(c0), "r"(c1) : "memory");
}
__device__ __forceinline__ bool elect_one() {
  uint32_t p;
  asm volatile("{.reg .pred q; elect.sync _|q, 0xffffffff; selp.u32 %0, 1, 0, q;}" : "=r"(p));
  return p;
}
__device__ __forceinline__ void pdl_wait() { asm volatile("griddepcontrol.wait;" ::: "memory"); }
__device__ __forceinline__ void pdl_launch() { asm volatile("griddepcontrol.launch_dependents;" ::: "memory"); }
__device__ __forceinline__ void fence_async_smem() { asm volatile("fence.proxy.async.shared::cta;" ::: "memory"); }
__device__ __forceinline__ void fence_bar_init() { asm volatile("fence.mbarrier_init.release.cluster;" ::: "memory"); }
__device__ __forceinline__ void named_sync(int id, int n) { asm volatile("bar.sync %0, %1;" ::"r"(id), "r"(n) : "memory"); }
__device__ __forceinline__ void wg_fence() { asm volatile("wgmma.fence.sync.aligned;" ::: "memory"); }
__device__ __forceinline__ void wg_commit() { asm volatile("wgmma.commit_group.sync.aligned;" ::: "memory"); }
template <int N> __device__ __forceinline__ void wg_wait() { asm volatile("wgmma.wait_group.sync.aligned %0;" ::"n"(N) : "memory"); }
template <int N> __device__ __forceinline__ void pin(float (&d)[N]) {
#pragma unroll
  for (int i = 0; i < N; i++) asm volatile("" : "+f"(d[i])::"memory");
}
template <int N> __device__ __forceinline__ void pin(uint32_t (&d)[N]) {
#pragma unroll
  for (int i = 0; i < N; i++) asm volatile("" : "+r"(d[i])::"memory");
}
__device__ __forceinline__ uint64_t mkdesc(uint32_t addr, uint32_t lbo, uint32_t sbo, uint64_t swz) {
  return (uint64_t)((addr & 0x3FFFF) >> 4) | ((uint64_t)(lbo >> 4) << 16) | ((uint64_t)(sbo >> 4) << 32) | (swz << 62);
}
__device__ __forceinline__ uint32_t pack_bf16(float lo, float hi) {
  uint32_t d; asm("cvt.rn.bf16x2.f32 %0, %1, %2;" : "=r"(d) : "f"(hi), "f"(lo)); return d;
}
__device__ __forceinline__ uint32_t pack_f16(float lo, float hi) {
  uint32_t d; asm("cvt.rn.f16x2.f32 %0, %1, %2;" : "=r"(d) : "f"(hi), "f"(lo)); return d;
}
__device__ __forceinline__ float bf_lo(uint32_t v) { return __uint_as_float(v << 16); }
__device__ __forceinline__ float bf_hi(uint32_t v) { return __uint_as_float(v & 0xffff0000u); }
__device__ __forceinline__ void stsm4(uint32_t addr, uint32_t a, uint32_t b, uint32_t c, uint32_t d) {
  asm volatile("stmatrix.sync.aligned.m8n8.x4.shared.b16 [%0], {%1,%2,%3,%4};" ::"r"(addr), "r"(a), "r"(b), "r"(c), "r"(d) : "memory");
}
__device__ __forceinline__ void ldsm4(uint32_t addr, uint32_t& a, uint32_t& b, uint32_t& c, uint32_t& d) {
  asm volatile("ldmatrix.sync.aligned.m8n8.x4.shared.b16 {%0,%1,%2,%3}, [%4];" : "=r"(a), "=r"(b), "=r"(c), "=r"(d) : "r"(addr) : "memory");
}
__device__ __forceinline__ uint32_t hadd2_bf16(uint32_t a, uint32_t b) {
  uint32_t d; asm("add.rn.bf16x2 %0, %1, %2;" : "=r"(d) : "r"(a), "r"(b)); return d;
}
__device__ __forceinline__ uint4 lds128(uint32_t addr) {
  uint4 v; asm volatile("ld.shared.v4.u32 {%0,%1,%2,%3}, [%4];" : "=r"(v.x), "=r"(v.y), "=r"(v.z), "=r"(v.w) : "r"(addr) : "memory"); return v;
}

__device__ __forceinline__ void wgmma_qk_n64(float (&d)[32], uint64_t da, uint64_t db) {
  asm volatile("wgmma.mma_async.sync.aligned.m64n64k16.f32.f16.f16 "
      "{%0,%1,%2,%3,%4,%5,%6,%7,%8,%9,%10,%11,%12,%13,%14,%15,%16,%17,%18,%19,%20,%21,%22,%23,%24,%25,%26,%27,%28,%29,%30,%31}, "
      "%32, %33, 1, 1, 1, 0, 0;"
    : "+f"(d[0]), "+f"(d[1]), "+f"(d[2]), "+f"(d[3]), "+f"(d[4]), "+f"(d[5]), "+f"(d[6]), "+f"(d[7]), "+f"(d[8]),
      "+f"(d[9]), "+f"(d[10]), "+f"(d[11]), "+f"(d[12]), "+f"(d[13]), "+f"(d[14]), "+f"(d[15]), "+f"(d[16]),
      "+f"(d[17]), "+f"(d[18]), "+f"(d[19]), "+f"(d[20]), "+f"(d[21]), "+f"(d[22]), "+f"(d[23]), "+f"(d[24]),
      "+f"(d[25]), "+f"(d[26]), "+f"(d[27]), "+f"(d[28]), "+f"(d[29]), "+f"(d[30]), "+f"(d[31])
    : "l"(da), "l"(db));
}
__device__ __forceinline__ void wgmma_pv_n24(float (&d)[12], uint32_t a0, uint32_t a1, uint32_t a2, uint32_t a3, uint64_t db) {
  asm volatile("wgmma.mma_async.sync.aligned.m64n24k16.f32.bf16.bf16 "
      "{%0,%1,%2,%3,%4,%5,%6,%7,%8,%9,%10,%11}, "
      "{%12,%13,%14,%15}, %16, 1, 1, 1, 1;"
    : "+f"(d[0]), "+f"(d[1]), "+f"(d[2]), "+f"(d[3]), "+f"(d[4]), "+f"(d[5]), "+f"(d[6]), "+f"(d[7]), "+f"(d[8]),
      "+f"(d[9]), "+f"(d[10]), "+f"(d[11])
    : "r"(a0), "r"(a1), "r"(a2), "r"(a3), "l"(db));
}
__device__ __forceinline__ void wgmma_gemm_n64(float (&d)[32], uint64_t da, uint64_t db) {
  asm volatile("wgmma.mma_async.sync.aligned.m64n64k16.f32.bf16.bf16 "
      "{%0,%1,%2,%3,%4,%5,%6,%7,%8,%9,%10,%11,%12,%13,%14,%15,%16,%17,%18,%19,%20,%21,%22,%23,%24,%25,%26,%27,%28,%29,%30,%31}, "
      "%32, %33, 1, 1, 1, 0, 1;"
    : "+f"(d[0]), "+f"(d[1]), "+f"(d[2]), "+f"(d[3]), "+f"(d[4]), "+f"(d[5]), "+f"(d[6]), "+f"(d[7]), "+f"(d[8]),
      "+f"(d[9]), "+f"(d[10]), "+f"(d[11]), "+f"(d[12]), "+f"(d[13]), "+f"(d[14]), "+f"(d[15]), "+f"(d[16]),
      "+f"(d[17]), "+f"(d[18]), "+f"(d[19]), "+f"(d[20]), "+f"(d[21]), "+f"(d[22]), "+f"(d[23]), "+f"(d[24]),
      "+f"(d[25]), "+f"(d[26]), "+f"(d[27]), "+f"(d[28]), "+f"(d[29]), "+f"(d[30]), "+f"(d[31])
    : "l"(da), "l"(db));
}
__device__ __forceinline__ void wgmma_gemm_n192(float (&d)[96], uint64_t da, uint64_t db) {
  asm volatile("wgmma.mma_async.sync.aligned.m64n192k16.f32.bf16.bf16 "
      "{%0,%1,%2,%3,%4,%5,%6,%7,%8,%9,%10,%11,%12,%13,%14,%15,%16,%17,%18,%19,%20,%21,%22,%23,%24,%25,%26,%27,%28,%29,%30,%31,%32,%33,%34,%35,%36,%37,%38,%39,%40,%41,%42,%43,%44,%45,%46,%47,%48,%49,%50,%51,%52,%53,%54,%55,%56,%57,%58,%59,%60,%61,%62,%63,%64,%65,%66,%67,%68,%69,%70,%71,%72,%73,%74,%75,%76,%77,%78,%79,%80,%81,%82,%83,%84,%85,%86,%87,%88,%89,%90,%91,%92,%93,%94,%95}, "
      "%96, %97, 1, 1, 1, 0, 1;"
    : "+f"(d[0]), "+f"(d[1]), "+f"(d[2]), "+f"(d[3]), "+f"(d[4]), "+f"(d[5]), "+f"(d[6]), "+f"(d[7]), "+f"(d[8]),
      "+f"(d[9]), "+f"(d[10]), "+f"(d[11]), "+f"(d[12]), "+f"(d[13]), "+f"(d[14]), "+f"(d[15]), "+f"(d[16]),
      "+f"(d[17]), "+f"(d[18]), "+f"(d[19]), "+f"(d[20]), "+f"(d[21]), "+f"(d[22]), "+f"(d[23]), "+f"(d[24]),
      "+f"(d[25]), "+f"(d[26]), "+f"(d[27]), "+f"(d[28]), "+f"(d[29]), "+f"(d[30]), "+f"(d[31]), "+f"(d[32]),
      "+f"(d[33]), "+f"(d[34]), "+f"(d[35]), "+f"(d[36]), "+f"(d[37]), "+f"(d[38]), "+f"(d[39]), "+f"(d[40]),
      "+f"(d[41]), "+f"(d[42]), "+f"(d[43]), "+f"(d[44]), "+f"(d[45]), "+f"(d[46]), "+f"(d[47]), "+f"(d[48]),
      "+f"(d[49]), "+f"(d[50]), "+f"(d[51]), "+f"(d[52]), "+f"(d[53]), "+f"(d[54]), "+f"(d[55]), "+f"(d[56]),
      "+f"(d[57]), "+f"(d[58]), "+f"(d[59]), "+f"(d[60]), "+f"(d[61]), "+f"(d[62]), "+f"(d[63]), "+f"(d[64]),
      "+f"(d[65]), "+f"(d[66]), "+f"(d[67]), "+f"(d[68]), "+f"(d[69]), "+f"(d[70]), "+f"(d[71]), "+f"(d[72]),
      "+f"(d[73]), "+f"(d[74]), "+f"(d[75]), "+f"(d[76]), "+f"(d[77]), "+f"(d[78]), "+f"(d[79]), "+f"(d[80]),
      "+f"(d[81]), "+f"(d[82]), "+f"(d[83]), "+f"(d[84]), "+f"(d[85]), "+f"(d[86]), "+f"(d[87]), "+f"(d[88]),
      "+f"(d[89]), "+f"(d[90]), "+f"(d[91]), "+f"(d[92]), "+f"(d[93]), "+f"(d[94]), "+f"(d[95])
    : "l"(da), "l"(db));
}

constexpr float QSCALE = 0.25f * 1.4426950408889634f;
constexpr float LN_EPS = 1e-5f;

__device__ __forceinline__ void row_stats(int layer, int row, float& mu, float& rstd) {
  const float4* p = reinterpret_cast<const float4*>(g_stats + (layer * S_ + row) * 8);
  float4 a = __ldcg(p), b = __ldcg(p + 1), c = __ldcg(p + 2), d = __ldcg(p + 3);
  float s = (a.x + a.z) + (b.x + b.z) + (c.x + c.z) + (d.x + d.z);
  float q = (a.y + a.w) + (b.y + b.w) + (c.y + c.w) + (d.y + d.w);
  mu = s * (1.f / D_);
  float var = fmaxf(q * (1.f / D_) - mu * mu, 0.f);
  rstd = rsqrtf(var + LN_EPS);
}

__global__ void __launch_bounds__(256) prep_kernel(const __nv_bfloat16* __restrict__ x, const __nv_bfloat16* __restrict__ wqkv,
                                                   const __nv_bfloat16* __restrict__ wq, const __nv_bfloat16* __restrict__ wk,
                                                   const __nv_bfloat16* __restrict__ wv) {
  TM(0, 0);
  pdl_launch();
  __shared__ float red[8][16];
  const int b = blockIdx.x, tid = threadIdx.x, lane = tid & 31, warp = tid >> 5;
  {
    const __nv_bfloat16* w; int ld, out;
    if (b < 96) { w = wqkv + b * 16; ld = 1536; out = b * 16; }
    else if (b < 128) { w = wq + (b - 96) * 16; ld = 512; out = 1536 + (b - 96) * 16; }
    else { w = (b == 128) ? wk : wv; ld = 16; out = 2048 + (b - 128) * 16; }
    const int half = tid & 1, r0 = tid >> 1;
    float acc[8];
#pragma unroll
    for (int i = 0; i < 8; i++) acc[i] = 0.f;
#pragma unroll
    for (int j = 0; j < 4; j++) {
      uint4 v = __ldg(reinterpret_cast<const uint4*>(w + (size_t)(r0 + 128 * j) * ld + half * 8));
      if (b >= 128) *reinterpret_cast<uint4*>(g_wkv + (r0 + 128 * j) * 32 + (b - 128) * 16 + half * 8) = v;
      acc[0] += bf_lo(v.x); acc[1] += bf_hi(v.x); acc[2] += bf_lo(v.y); acc[3] += bf_hi(v.y);
      acc[4] += bf_lo(v.z); acc[5] += bf_hi(v.z); acc[6] += bf_lo(v.w); acc[7] += bf_hi(v.w);
    }
#pragma unroll
    for (int i = 0; i < 8; i++) {
#pragma unroll
      for (int o = 2; o < 32; o <<= 1) acc[i] += __shfl_xor_sync(0xffffffffu, acc[i], o);
    }
    if (lane < 2) {
#pragma unroll
      for (int i = 0; i < 8; i++) red[warp][lane * 8 + i] = acc[i];
    }
    __syncthreads();
    if (tid < 16) {
      float s = 0.f;
#pragma unroll
      for (int w8 = 0; w8 < 8; w8++) s += red[w8][tid];
      g_colsum[out + tid] = s;
    }
    if (b == 129 && tid >= 32 && tid < 64) g_colsum[2048 + tid] = 0.f;
  }
  if (b < 128) {
#pragma unroll
    for (int j = 0; j < 2; j++) {
      const int row = b * 16 + warp * 2 + j;
      const uint4* p = reinterpret_cast<const uint4*>(x + (size_t)row * D_ + lane * 16);
      uint4 v0 = __ldg(p), v1 = __ldg(p + 1);
      uint32_t u[8] = {v0.x, v0.y, v0.z, v0.w, v1.x, v1.y, v1.z, v1.w};
      float s = 0.f, q = 0.f;
#pragma unroll
      for (int i = 0; i < 8; i++) {
        float a = bf_lo(u[i]), c = bf_hi(u[i]);
        s += a + c; q = fmaf(a, a, fmaf(c, c, q));
      }
      s += __shfl_xor_sync(0xffffffffu, s, 1); q += __shfl_xor_sync(0xffffffffu, q, 1);
      s += __shfl_xor_sync(0xffffffffu, s, 2); q += __shfl_xor_sync(0xffffffffu, q, 2);
      if ((lane & 3) == 0) g_stats[row * 8 + (lane >> 2)] = make_float2(s, q);
    }
  }
  TM(0, 4);
}

__device__ __forceinline__ int tok0(int r, int rb) { return (rb >> 2) * 512 + r * 256 + (rb & 3) * 64; }
__device__ __forceinline__ int key_pos(int token) {
  const int r = (token >> 8) & 1, rb = ((token >> 9) << 2) | ((token >> 6) & 3), row = token & 63;
  return (16 * r + (row >> 2)) * 64 + rb * 4 + (row & 3);
}
__device__ __forceinline__ float sq_norm16(const uint4& a, const uint4& b) {
  const uint32_t u[8] = {a.x, a.y, a.z, a.w, b.x, b.y, b.z, b.w};
  __half2 n = __hmul2(*reinterpret_cast<const __half2*>(&u[0]), *reinterpret_cast<const __half2*>(&u[0]));
#pragma unroll
  for (int i = 1; i < 8; i++) n = __hfma2(*reinterpret_cast<const __half2*>(&u[i]), *reinterpret_cast<const __half2*>(&u[i]), n);
  return __low2float(n) + __high2float(n);
}
__device__ __forceinline__ uint32_t hsub2(uint32_t a, uint32_t b) {
  uint32_t d; asm("sub.rn.f16x2 %0, %1, %2;" : "=r"(d) : "r"(a), "r"(b)); return d;
}
__device__ __forceinline__ void proj_store(uint32_t a, uint32_t ap, int type, int layer, int head, int token) {
  const uint4 v0 = lds128(a), v1 = lds128(a + 16);
  const size_t hb = (size_t)((layer & 1) * H_ + head) * (S_ * 2);
  if (type == 2) {
    uint4* dst = g_v + hb + key_pos(token);
    dst[0] = v0; dst[S_] = v1;
    return;
  }
  if (type == 0) {
    uint4* dst = g_q + hb + (token >> 3) * 16 + (token & 7);
    dst[0] = v0; dst[8] = v1;
  } else {
    uint4 d0 = v0, d1 = v1;
    if (ap) {
      const uint4 p0 = lds128(ap), p1 = lds128(ap + 16);
      d0 = make_uint4(hsub2(v0.x, p0.x), hsub2(v0.y, p0.y), hsub2(v0.z, p0.z), hsub2(v0.w, p0.w));
      d1 = make_uint4(hsub2(v1.x, p1.x), hsub2(v1.y, p1.y), hsub2(v1.z, p1.z), hsub2(v1.w, p1.w));
    }
    const int pos = key_pos(token);
    uint4* dst = g_k + hb + (pos >> 3) * 16 + (pos & 7);
    dst[0] = d0; dst[8] = d1;
  }
  const unsigned m = __reduce_max_sync(0xffffffffu, __float_as_uint(sq_norm16(v0, v1)) & 0x7fffffffu);
  if ((threadIdx.x & 31) == 0) g_nrm[((layer * 2 + type) * H_ + head) * 64 + (token >> 5)] = __uint_as_float(m);
}
template <bool F16, int N>
__device__ __forceinline__ void proj_stage(const float (&acc)[N], int j  , uint32_t addr, const float* cs,
                                           float mu0, float f0, float mu1, float f1) {
  uint32_t r[4];
#pragma unroll
  for (int e = 0; e < 2; e++) {
    const float2 c = *reinterpret_cast<const float2*>(cs + (j + e) * 8);
    const float a0 = fmaf(-mu0, c.x, acc[(j + e) * 4 + 0]) * f0, a1 = fmaf(-mu0, c.y, acc[(j + e) * 4 + 1]) * f0;
    const float a2 = fmaf(-mu1, c.x, acc[(j + e) * 4 + 2]) * f1, a3 = fmaf(-mu1, c.y, acc[(j + e) * 4 + 3]) * f1;
    r[e * 2] = F16 ? pack_f16(a0, a1) : pack_bf16(a0, a1);
    r[e * 2 + 1] = F16 ? pack_f16(a2, a3) : pack_bf16(a2, a3);
  }
  stsm4(addr + j * 16, r[0], r[1], r[2], r[3]);
}

constexpr int G1A_NS = 5, G1A_STAGE = 16384 + 3 * 8192, G1A_PITCH = 400;
constexpr int G1A_SMEM = G1A_NS * G1A_STAGE + 1024 + 192 * 4 + 128;
__global__ void __launch_bounds__(288, 1) g1a_kernel(const __grid_constant__ CUtensorMap mx, const __grid_constant__ CUtensorMap mw) {
  extern __shared__ uint8_t smem_raw[];
  const uint32_t sbase = (s2u(smem_raw) + 1023) & ~1023u;
  const uint32_t s_cs = sbase + G1A_NS * G1A_STAGE, s_bar = s_cs + 192 * 4;
  float* cs = reinterpret_cast<float*>(smem_raw + (s_cs - s2u(smem_raw)));
  const int tid = threadIdx.x, warp = tid >> 5, lane = tid & 31;
  const int nb = blockIdx.x & 7, rb = blockIdx.x >> 3;
  TM(1, 0);
  if (tid == 0) {
    for (int i = 0; i < G1A_NS; i++) { mbar_init(s_bar + i * 8, 1); mbar_init(s_bar + 40 + i * 8, 2); }
    fence_bar_init();
  }
  __syncthreads();
  if (warp == 8) {
    if (lane == 0) {
      for (int c = 0; c < 8; c++) {
        const int s = c < G1A_NS ? c : c - G1A_NS;
        const uint32_t st = sbase + s * G1A_STAGE, bar = s_bar + s * 8;
        if (c >= G1A_NS) mbar_wait(s_bar + 40 + s * 8, 0);
        mbar_expect(bar, G1A_STAGE);
        tma_load(st, &mx, c * 64, tok0(0, rb), bar);
        tma_load(st + 8192, &mx, c * 64, tok0(1, rb), bar);
        for (int j = 0; j < 3; j++) tma_load(st + 16384 + j * 8192, &mw, nb * 192 + j * 64, c * 64, bar);
      }
    }
    return;
  }
  const int wg = warp >> 2;
  float acc[96];
#pragma unroll
  for (int i = 0; i < 96; i++) acc[i] = 0.f;
  pin(acc);
#pragma unroll 1
  for (int c = 0; c < 8; c++) {
    const int s = c < G1A_NS ? c : c - G1A_NS;
    mbar_wait(s_bar + s * 8, c >= G1A_NS);
    if (c == 0) TM(1, 2);
    const uint32_t st = sbase + s * G1A_STAGE;
    const uint64_t da = mkdesc(st + wg * 8192, 16, 1024, 1), db = mkdesc(st + 16384, 8192, 1024, 1);
    wg_fence();
#pragma unroll
    for (int k = 0; k < 4; k++) wgmma_gemm_n192(acc, da + k * 2, db + k * 128);
    wg_commit();
    if (c >= 1 && c <= 3) { wg_wait<1>(); if ((tid & 127) == 0) mbar_arrive(s_bar + 40 + (c - 1) * 8); }
    if (c == 5) {
      pdl_wait();
      pdl_launch();
      if (tid < 192) cs[tid] = __ldcg(g_colsum + nb * 192 + tid);
    }
  }
  float mu0, rs0, mu1, rs1;
  const int row0 = tok0(wg, rb) + (warp & 3) * 16 + (lane >> 2);
  row_stats(0, row0, mu0, rs0); row_stats(0, row0 + 8, mu1, rs1);
  wg_wait<0>();
  pin(acc);
  TM(1, 3);
  named_sync(1, 256);
  {
    const uint32_t addr = sbase + (wg * 64 + (warp & 3) * 16 + (lane & 15)) * G1A_PITCH + (lane >> 4) * 16;
#pragma unroll
    for (int j = 0; j < 24; j += 2) {
      const int type = (nb * 12 + (j >> 1)) >> 5;
      const float sc = type == 0 ? QSCALE : 1.f;
      if (type == 2) proj_stage<false>(acc, j, addr, cs + (lane & 3) * 2, mu0, rs0, mu1, rs1);
      else proj_stage<true>(acc, j, addr, cs + (lane & 3) * 2, mu0, rs0 * sc, mu1, rs1 * sc);
    }
  }
  named_sync(1, 256);
#pragma unroll
  for (int it = 0; it < 6; it++) {
    const int item = warp + it * 8, hh = item >> 2, trow = (item & 3) * 32 + lane;
    const int hg = nb * 12 + hh;
    const uint32_t a = sbase + trow * G1A_PITCH + hh * 32;
    proj_store(a, trow >= 4 ? a - 4 * G1A_PITCH : 0u, hg >> 5, 0, hg & 31, tok0(trow >> 6, rb) + (trow & 63));
  }
  TM(1, 4);
}

constexpr uint32_t MUFU_MASK = 0xF800u;
constexpr float EXP_MAGIC = 383.0f + 0.65f / 128.0f;
constexpr uint32_t POLY_A = 0x5a835a83u, POLY_B = 0x92a192a1u, POLY_C = 0x800b800bu;
constexpr float SCORE_LIMIT = 116.f;

__device__ __forceinline__ void exp_step(const float (&s)[32], uint32_t (&p)[16], uint32_t pb) {
#pragma unroll
  for (int i = 0; i < 16; i++) {
    if ((MUFU_MASK >> i) & 1) {
      float a, b;
      asm("ex2.approx.ftz.f32 %0, %1;" : "=f"(a) : "f"(s[2 * i]));
      asm("ex2.approx.ftz.f32 %0, %1;" : "=f"(b) : "f"(s[2 * i + 1]));
      p[i] = pack_bf16(a, b);
    } else {
      uint32_t z, u, h;
      asm("prmt.b32 %0, %1, %2, 0x6521;" : "=r"(z) : "r"(__float_as_uint(s[2 * i])), "r"(__float_as_uint(s[2 * i + 1])));
      asm("fma.rn.f16x2 %0, %1, %2, %3;" : "=r"(u) : "r"(z & 0x007f007fu), "r"(POLY_A), "r"(pb));
      asm("fma.rn.f16x2 %0, %1, %1, %2;" : "=r"(h) : "r"(u), "r"(POLY_C));
      p[i] = z - h;
    }
  }
}

template <bool PV>
__device__ __forceinline__ void att_step(float (&s)[32], float (&o)[12], uint32_t (&pin_)[16], uint32_t (&pout)[16], uint64_t dq,
                                         uint64_t dk, uint64_t dv, uint32_t pb) {
  pin(s);
  if (PV) pin(pin_);
  wg_fence();
  wgmma_qk_n64(s, dq, dk);
  wg_commit();
  if (PV) {
#pragma unroll
    for (int j = 0; j < 4; j++) wgmma_pv_n24(o, pin_[4 * j], pin_[4 * j + 1], pin_[4 * j + 2], pin_[4 * j + 3], dv + j * 16);
    wg_commit();
    wg_wait<1>();
  } else {
    wg_wait<0>();
  }
  pin(s);
  exp_step(s, pout, pb);
  pin(pout);
}

constexpr int M_STAGE = 0;
constexpr int M_STG = 65536, STG_PITCH = 144;
constexpr int M_KV = 74752;
constexpr int M_Q = M_KV + 17 * 8192;
constexpr int M_CS = M_Q + 16384, M_KTAIL = M_CS + 768, M_ROW = M_KTAIL + 512, M_BAR = M_ROW + 512;
constexpr int MEGA_SMEM = M_BAR + 256;
__device__ __forceinline__ int k_unit(int j) { return j < 2 ? 7 + 2 * j : j - 2; }
__device__ __forceinline__ int v0_unit(int b) { return b == 0 ? 14 : 12 - 2 * b; }
__device__ __forceinline__ int v_stride(int b) { return b == 0 ? 1 : b + 2; }
constexpr int B_FULL = 0, B_EMPTY = 32, B_KV = 64, B_Q = 80, B_FREE0 = 96, B_ODONE = 104, B_RES = 120, B_PRE = 128,
              B_TURN = 136, B_EPI = 168;

struct MegaParams {
  CUtensorMap m[8];
  const __nv_bfloat16* x0;
  const __nv_bfloat16* wqkv; const __nv_bfloat16* wq; const __nv_bfloat16* wk;
  __nv_bfloat16* out;
};

__device__ __forceinline__ void cnt_signal(int idx) {
  if (elect_one()) asm volatile("red.release.gpu.global.add.u32 [%0], 1;" ::"l"(g_cnt + idx) : "memory");
}
__device__ __forceinline__ void cnt_wait(int idx, unsigned target) {
  unsigned v;
  int it = 0;
  while (true) {
    asm volatile("ld.acquire.gpu.global.u32 %0, [%1];" : "=r"(v) : "l"(g_cnt + idx) : "memory");
    if (v >= target) break;
    if (++it > (1 << 24)) __trap();
  }
  asm volatile("fence.proxy.async.global;" ::: "memory");
}

__device__ __forceinline__ void att_fallback(const MegaParams& P, int layer, int head, int row0, __nv_bfloat16* sk, int bar_id) {
  const int t = threadIdx.x & 127, hf = t & 1;
  const __nv_bfloat16* x = layer == 0 ? P.x0 : g_x + (size_t)(layer - 1) * S_ * D_;
  const bool mqa = layer & 1;
  const __nv_bfloat16* vimg = reinterpret_cast<const __nv_bfloat16*>(g_v + (size_t)((layer & 1) * H_ + (mqa ? 0 : head)) * (S_ * 2));
  float q[16], o[16], acc[16];
  float m = -INFINITY, l = 0.f;
#pragma unroll
  for (int d = 0; d < 16; d++) { o[d] = 0.f; q[d] = 0.f; }
#pragma unroll 1
  for (int ch = -1; ch < 32; ch++) {
    const int token = ch < 0 ? row0 + (t >> 1) : ch * 64 + (t >> 1);
    const __nv_bfloat16* w = ch < 0 ? (mqa ? P.wq : P.wqkv) + head * 16 : (mqa ? P.wk : P.wqkv + 512 + head * 16);
    const int ld = mqa ? (ch < 0 ? 512 : 16) : 1536;
    float mu, rs;
    row_stats(layer, token, mu, rs);
#pragma unroll
    for (int d = 0; d < 16; d++) acc[d] = 0.f;
#pragma unroll 1
    for (int k = hf * 256; k < hf * 256 + 256; k++) {
      const unsigned short xr = __ldcg(reinterpret_cast<const unsigned short*>(x) + (size_t)token * D_ + k);
      const float xn = __bfloat162float(__float2bfloat16((__uint_as_float((uint32_t)xr << 16) - mu) * rs));
#pragma unroll
      for (int d = 0; d < 16; d++) acc[d] = fmaf(xn, __bfloat162float(w[(size_t)k * ld + d]), acc[d]);
    }
#pragma unroll
    for (int d = 0; d < 16; d++) acc[d] = __bfloat162float(__float2bfloat16(acc[d] + __shfl_xor_sync(0xffffffffu, acc[d], 1)));
    if (ch < 0) {
#pragma unroll
      for (int d = 0; d < 16; d++) q[d] = acc[d];
      continue;
    }
    named_sync(bar_id, 128);
    if (hf == 0) {
#pragma unroll
      for (int d = 0; d < 16; d++) sk[(t >> 1) * 16 + d] = __float2bfloat16(acc[d]);
    }
    named_sync(bar_id, 128);
#pragma unroll 1
    for (int j = hf * 32; j < hf * 32 + 32; j++) {
      float sc = 0.f;
#pragma unroll
      for (int d = 0; d < 16; d++) sc = fmaf(q[d], __bfloat162float(sk[j * 16 + d]), sc);
      sc *= 0.25f;
      if (sc > m || sc != sc) {
        const float a = __expf(m - sc);
        l *= a;
#pragma unroll
        for (int d = 0; d < 16; d++) o[d] *= a;
        m = sc;
      }
      const float p = __expf(sc - m);
      l += p;
      const int pos = key_pos(ch * 64 + j);
#pragma unroll
      for (int d = 0; d < 16; d++) {
        const unsigned short vr = __ldcg(reinterpret_cast<const unsigned short*>(vimg) + (d >> 3) * (S_ * 8) + pos * 8 + (d & 7));
        o[d] = fmaf(p, __uint_as_float((uint32_t)vr << 16), o[d]);
      }
    }
  }
  const float m2 = __shfl_xor_sync(0xffffffffu, m, 1), mm = fmaxf(m, m2), a = __expf(m - mm);
  l *= a; l += __shfl_xor_sync(0xffffffffu, l, 1);
  const float inv = 1.f / l;
  __nv_bfloat16* dst = g_o + (size_t)(row0 + (t >> 1)) * D_ + head * 16;
#pragma unroll
  for (int d = 0; d < 16; d++) {
    float v = o[d] * a; v += __shfl_xor_sync(0xffffffffu, v, 1);
    if ((d >> 3) == hf) dst[d] = __float2bfloat16(v * inv);
  }
}

__device__ __forceinline__ const CUtensorMap* b_map(const MegaParams& P, int code) {
  const int l = code >> 3, p = code & 3;
  return &P.m[p == 0 ? 5 + (l & 1) : ((l & 1) ? 2 : (p == 3 ? 3 : 4))];
}
__device__ __forceinline__ int b_col(int code) {
  const int p = code & 3, ct = blockIdx.x & 7;
  return p == 0 || p == 3 ? ct * 64 : ((code & 8) ? p * 512 + ct * 64 : 0);
}
__device__ __forceinline__ void issue_b(uint32_t sbase, const CUtensorMap* m, int col, int st, int c) {
  mbar_expect(sbase + M_BAR + B_FULL + st * 8, 16384);
  tma_load(sbase + M_STAGE + st * 16384 + 8192, m, col, c * 64, sbase + M_BAR + B_FULL + st * 8);
}
__device__ __forceinline__ void issue_a(uint32_t sbase, const CUtensorMap* m, int row, int st, int c) {
  tma_load(sbase + M_STAGE + st * 16384, m, c * 64, row, sbase + M_BAR + B_FULL + st * 8);
}
__device__ __forceinline__ void load_kv(uint32_t sbase, int l, int r) {
  const size_t hb = (size_t)((l & 1) * H_ + ((l & 1) ? 0 : blockIdx.x >> 2)) * 65536;
  const uint8_t* gk = reinterpret_cast<const uint8_t*>(g_k) + hb;
  const uint8_t* gv = reinterpret_cast<const uint8_t*>(g_v) + hb;
  const uint32_t bar = sbase + M_BAR + B_KV + r * 8;
  if (elect_one()) {
    mbar_expect(bar, 65536);
#pragma unroll
    for (int j = 0; j < 2; j++) {
      const int b = r * 2 + j;
      bulk_load(sbase + M_KV + k_unit(2 * b) * 8192, gk + b * 16384, 8192, bar);
      bulk_load(sbase + M_KV + v0_unit(b) * 8192, gv + b * 8192, 8192, bar);
      bulk_load(sbase + M_KV + (v0_unit(b) + v_stride(b)) * 8192, gv + 32768 + b * 8192, 8192, bar);
      bulk_load(sbase + M_KV + k_unit(2 * b + 1) * 8192, gk + b * 16384 + 8192, 8192, bar);
    }
  }
}
__device__ __forceinline__ void load_q(uint32_t sbase, int l, int r) {
  const uint32_t bar = sbase + M_BAR + B_Q + r * 8;
  if (elect_one()) {
    mbar_expect(bar, 8192);
    bulk_load(sbase + M_Q + r * 8192,
              reinterpret_cast<const uint8_t*>(g_q) + (size_t)((l & 1) * H_ + (blockIdx.x >> 2)) * 65536 + (blockIdx.x & 3) * 16384 + r * 8192,
              8192, bar);
  }
}

__device__ __forceinline__ bool pass_exists(int job, int p) {
  return p == 0 || (job < 6 && (p == 3 || (job & 2) || (p == 1 && (blockIdx.x & 7) == 0)));
}
__device__ __forceinline__ int next_pass(int code) {
  const int job = code >> 2, p = code & 3;
  if (p == 0 && pass_exists(job, 1)) return code + 1;
  if (p == 1 && pass_exists(job, 2)) return code + 1;
  if (p < 3 && pass_exists(job, 3)) return job * 4 + 3;
  return job * 4 + 4;
}
__device__ __forceinline__ int prev_pass(int code) {
  const int job = code >> 2, p = code & 3;
  if (p == 0) return job > 6 ? (job - 1) * 4 : (job - 1) * 4 + 3;
  if (p == 3 && pass_exists(job, 2)) return code - 1;
  if (p >= 2 && pass_exists(job, 1)) return job * 4 + 1;
  return job * 4;
}

__device__ __forceinline__ void proj_pass(const MegaParams& P, uint8_t* sm, uint32_t sbase, int code, int wg) {
  const uint32_t s_bar = sbase + M_BAR;
  const int prev = prev_pass(code);
  if (code > 0) mbar_wait(s_bar + B_TURN + (prev & 3) * 8, (prev >> 2) & 1);
  float acc[32];
#pragma unroll
  for (int i = 0; i < 32; i++) acc[i] = 0.f;
  pin(acc);
#pragma unroll 1
  for (int h = 0; h < 2; h++) {
    h = __shfl_sync(0xffffffffu, h, 0);
#pragma unroll
    for (int j = 0; j < 4; j++) {
      const uint32_t st = sbase + M_STAGE + j * 16384;
      mbar_wait(s_bar + B_FULL + j * 8, h);
      const uint64_t da = mkdesc(st, 16, 1024, 1), db = mkdesc(st + 8192, 8192, 1024, 1);
      wg_fence();
#pragma unroll
      for (int k = 0; k < 4; k++) wgmma_gemm_n64(acc, da + k * 2, db + k * 128);
      wg_commit();
      wg_wait<1>();
      if ((j > 0 || h == 1) && elect_one()) mbar_arrive(s_bar + B_EMPTY + ((j + 3) & 3) * 8);
    }
  }
  wg_wait<0>();
  pin(acc);
  if (elect_one()) { mbar_arrive(s_bar + B_EMPTY + 24); mbar_arrive(s_bar + B_TURN + (code & 3) * 8); }
  int t;
  asm volatile("mov.u32 %0, %%tid.x;" : "=r"(t));
  t &= 127;
  const int lane = t & 31, w4 = t >> 5;
  const int l = code >> 3, r = (code >> 2) & 1, p = code & 3;
  const int rb = blockIdx.x >> 3, ct = blockIdx.x & 7, row0 = tok0(r, rb);
  const uint32_t stg = sbase + M_STG;
  if (p == 0) {
    mbar_wait(s_bar + B_RES, r);
    const uint32_t ra = stg + (w4 * 16 + (lane & 15)) * 128;
    float s0 = 0.f, q0 = 0.f, s1 = 0.f, q1 = 0.f;
#pragma unroll
    for (int j = 0; j < 8; j += 2) {
      const uint32_t a = ra + (((j + (lane >> 4)) ^ (lane & 7)) << 4);
      uint32_t y[4];
      ldsm4(a, y[0], y[1], y[2], y[3]);
#pragma unroll
      for (int e = 0; e < 4; e++) {
        y[e] = hadd2_bf16(y[e], pack_bf16(acc[4 * j + 2 * e], acc[4 * j + 2 * e + 1]));
        const float lo = bf_lo(y[e]), hi = bf_hi(y[e]);
        if (e & 1) { s1 += lo + hi; q1 = fmaf(lo, lo, fmaf(hi, hi, q1)); }
        else { s0 += lo + hi; q0 = fmaf(lo, lo, fmaf(hi, hi, q0)); }
      }
      stsm4(a, y[0], y[1], y[2], y[3]);
    }
    __syncwarp();
    __nv_bfloat16* xout = (l == 3 ? P.out : g_x + (size_t)l * S_ * D_) + (size_t)(row0 + w4 * 16 + (lane >> 3)) * D_ + ct * 64 + (lane & 7) * 8;
#pragma unroll
    for (int i = 0; i < 4; i++) {
      const int rr = i * 4 + (lane >> 3);
      *reinterpret_cast<uint4*>(xout + (size_t)i * 4 * D_) = lds128(stg + (w4 * 16 + rr) * 128 + (((lane & 7) ^ (rr & 7)) << 4));
    }
    if (l < 3) {
#pragma unroll
      for (int o = 1; o < 4; o <<= 1) {
        s0 += __shfl_xor_sync(0xffffffffu, s0, o); q0 += __shfl_xor_sync(0xffffffffu, q0, o);
        s1 += __shfl_xor_sync(0xffffffffu, s1, o); q1 += __shfl_xor_sync(0xffffffffu, q1, o);
      }
      if ((lane & 3) == 0) {
        float2* st = g_stats + ((l + 1) * S_ + row0 + w4 * 16 + (lane >> 2)) * 8 + ct;
        st[0] = make_float2(s0, q0); st[64] = make_float2(s1, q1);
      }
    }
  } else {
    const bool kv = !(l & 1) && p == 1;
    const int type = p == 3 ? 0 : p;
    mbar_wait(s_bar + B_PRE, r);
    mbar_wait(s_bar + B_EPI + (prev & 3) * 8, (prev >> 2) & 1);
    const float2 st0 = reinterpret_cast<const float2*>(sm + M_ROW)[w4 * 16 + (lane >> 2)];
    const float2 st1 = reinterpret_cast<const float2*>(sm + M_ROW)[w4 * 16 + (lane >> 2) + 8];
    const float* cs = reinterpret_cast<const float*>(sm + M_CS) + (p - 1) * 64 + (lane & 3) * 2;
    const uint32_t saddr = stg + (w4 * 16 + (lane & 15)) * STG_PITCH + (lane >> 4) * 16;
    if (kv) {
      proj_stage<true>(acc, 0, saddr, cs, st0.x, st0.y, st1.x, st1.y);
      proj_stage<false>(acc, 2, saddr, cs, st0.x, st0.y, st1.x, st1.y);
    } else if (type == 2) {
#pragma unroll
      for (int j = 0; j < 8; j += 2) proj_stage<false>(acc, j, saddr, cs, st0.x, st0.y, st1.x, st1.y);
    } else {
      const float sc = type == 0 ? QSCALE : 1.f, f0 = st0.y * sc, f1 = st1.y * sc;
#pragma unroll
      for (int j = 0; j < 8; j += 2) proj_stage<true>(acc, j, saddr, cs, st0.x, f0, st1.x, f1);
    }
    named_sync(wg + 1, 128);
    const int row = t & 63;
#pragma unroll
    for (int i = 0; i < 2; i++) {
      if (kv && i == 1) break;
      const int hh = 2 * i + (t >> 6);
      const uint32_t a = stg + row * STG_PITCH + hh * 32;
      const uint32_t ap = row >= 4 ? a - 4 * STG_PITCH : (r ? sbase + M_KTAIL + row * 128 + hh * 32 : 0u);
      proj_store(a, ap, kv ? 1 + hh : type, l + 1, kv ? 0 : ct * 4 + hh, row0 + row);
    }
    if (p == 1 && r == 0 && t < 32)
      *reinterpret_cast<uint4*>(sm + M_KTAIL + t * 16) = lds128(stg + (60 + (t >> 3)) * STG_PITCH + (t & 7) * 16);
  }
  __syncwarp();
  if (lane == 0) mbar_arrive(s_bar + B_EPI + p * 8);
}

__global__ void __launch_bounds__(640, 1) mega_kernel(const __grid_constant__ MegaParams P) {
  extern __shared__ __align__(1024) uint8_t sm[];
  const uint32_t sbase = s2u(sm);
  if (sbase & 1023) __trap();
  const uint32_t s_bar = sbase + M_BAR;
  const int tid = threadIdx.x, warp = tid >> 5, lane = tid & 31;
  TM(2, 0);
  if (tid == 0) {
    for (int i = 0; i < 4; i++) {
      mbar_init(s_bar + B_FULL + i * 8, 1); mbar_init(s_bar + B_EMPTY + i * 8, 4);
      mbar_init(s_bar + B_TURN + i * 8, 4); mbar_init(s_bar + B_EPI + i * 8, 4);
    }
    for (int i = 0; i < 2; i++) { mbar_init(s_bar + B_KV + i * 8, 1); mbar_init(s_bar + B_Q + i * 8, 1); mbar_init(s_bar + B_ODONE + i * 8, 16); }
    mbar_init(s_bar + B_FREE0, 16);
    mbar_init(s_bar + B_RES, 1);
    mbar_init(s_bar + B_PRE, 1);
    fence_bar_init();
  }
  if (tid < 512) *reinterpret_cast<uint4*>(sm + M_KV + 16 * 8192 + tid * 16) = make_uint4(0x3f803f80u, 0x3f803f80u, 0x3f803f80u, 0x3f803f80u);
  fence_async_smem();
  __syncthreads();
  const int wg = __shfl_sync(0xffffffffu, warp >> 2, 0);

  if (wg < 4) {
    asm volatile("setmaxnreg.inc.sync.aligned.u32 112;");
    pdl_wait();
    const int head = blockIdx.x >> 2, quarter = blockIdx.x & 3;
    uint32_t pb = POLY_B;
    asm volatile("" : "+r"(pb));
    float s[32], o[12];
#pragma unroll
    for (int i = 0; i < 32; i++) s[i] = ((MUFU_MASK >> (i >> 1)) & 1) ? 0.f : EXP_MAGIC;
#pragma unroll
    for (int i = 0; i < 12; i++) o[i] = 0.f;
#pragma unroll 1
    for (int it = 0; it <= 32; it++) {
      it = __shfl_sync(0xffffffffu, it, 0);
      const int lr = it >> 2, b = it & 3, rnd = lr & 1, layer = lr >> 1;
      const uint32_t par = layer & 1;
      {
        const int job = lr - 1, p = (wg - job) & 3;
        if (job >= 0 && b == ((p + 1) >> 1) && pass_exists(job, p)) {
          TM3(24 + job * 4 + p, 0);
          proj_pass(P, sm, sbase, job * 4 + p, wg);
          TM3(24 + job * 4 + p, 1);
        }
      }
      if (it == 32) break;
      if (b == 0) mbar_wait(s_bar + B_Q + rnd * 8, par);
      if (b == 2) TM1(3 + lr, 1);
      mbar_wait(s_bar + B_KV + (b >> 1) * 8, par);
      if (b == 0) TM1(3 + lr, 0);
      if (b == 2) TM1(3 + lr, 2);
      {
        uint32_t p0[16], p1[16];
        const uint64_t dq = mkdesc(sbase + M_Q + rnd * 8192 + wg * 2048, 128, 256, 0);
        const uint64_t dk0 = mkdesc(sbase + M_KV + k_unit(2 * b) * 8192, 128, 256, 0);
        const uint64_t dk1 = mkdesc(sbase + M_KV + k_unit(2 * b + 1) * 8192, 128, 256, 0);
        const uint64_t dv = mkdesc(sbase + M_KV + v0_unit(b) * 8192, 128, v_stride(b) * 8192, 0);
        pin(o);
        att_step<false>(s, o, p1, p0, dq, dk0, dv, pb);
        att_step<true>(s, o, p0, p1, dq, dk0 + 128, dv, pb);
        att_step<true>(s, o, p1, p0, dq, dk0 + 256, dv + 64, pb);
        att_step<true>(s, o, p0, p1, dq, dk0 + 384, dv + 128, pb);
        att_step<true>(s, o, p1, p0, dq, dk1, dv + 192, pb);
        att_step<true>(s, o, p0, p1, dq, dk1 + 128, dv + 256, pb);
        att_step<true>(s, o, p1, p0, dq, dk1 + 256, dv + 320, pb);
        att_step<true>(s, o, p0, p1, dq, dk1 + 384, dv + 384, pb);
        pin(p1);
        wg_fence();
#pragma unroll
        for (int j = 0; j < 4; j++) wgmma_pv_n24(o, p1[4 * j], p1[4 * j + 1], p1[4 * j + 2], p1[4 * j + 3], dv + 448 + j * 16);
        wg_commit();
        wg_wait<0>();
        pin(o); pin(s);
      }
      if (b == 1 && rnd == 1 && elect_one()) mbar_arrive(s_bar + B_FREE0);
      if (b == 3) {
        int t;
        asm volatile("mov.u32 %0, %%tid.x;" : "=r"(t));
        const int ln = t & 31;
        const int row0 = quarter * 512 + rnd * 256 + wg * 64;
        const float* nq = g_nrm + (layer * 2 * H_ + head) * 64 + (row0 >> 5);
        const float* nk = g_nrm + ((layer * 2 + 1) * H_ + (par ? 0 : head)) * 64;
        const unsigned qn = max(__float_as_uint(__ldcg(nq)), __float_as_uint(__ldcg(nq + 1)));
        const unsigned kn = __reduce_max_sync(0xffffffffu, max(__float_as_uint(__ldcg(nk + ln)), __float_as_uint(__ldcg(nk + 32 + ln))));
        const float l0 = o[8], l1 = o[10];
        float mx = 0.f;
#pragma unroll
        for (int i = 0; i < 8; i++) mx += fabsf(o[i]);
        const float i0 = __fdividef(1.f, l0), i1 = __fdividef(1.f, l1);
        __nv_bfloat16* dst = g_o + (size_t)(row0 + ((t >> 5) & 3) * 16 + (ln >> 2)) * D_ + head * 16 + (ln & 3) * 2;
        *reinterpret_cast<uint32_t*>(dst) = pack_bf16(o[0] * i0, o[1] * i0);
        *reinterpret_cast<uint32_t*>(dst + 8) = pack_bf16(o[4] * i0, o[5] * i0);
        *reinterpret_cast<uint32_t*>(dst + 8 * D_) = pack_bf16(o[2] * i1, o[3] * i1);
        *reinterpret_cast<uint32_t*>(dst + 8 * D_ + 8) = pack_bf16(o[6] * i1, o[7] * i1);
        const bool ok = __uint_as_float(qn) * __uint_as_float(kn) <= SCORE_LIMIT * SCORE_LIMIT && l0 >= 1e-18f && l0 <= 1e37f &&
                        l1 >= 1e-18f && l1 <= 1e37f && mx <= 3e38f;
        uint32_t bad;
        asm volatile("{.reg .pred p, q; setp.eq.u32 p, %1, 0; barrier.red.or.pred.aligned q, %2, 128, p; selp.u32 %0, 1, 0, q;}"
                     : "=r"(bad) : "r"((uint32_t)ok), "r"(wg + 1) : "memory");
        if (bad) {
          att_fallback(P, layer, head, row0, reinterpret_cast<__nv_bfloat16*>(sm + M_Q + rnd * 8192 + wg * 2048), wg + 1);
          fence_async_smem();
        }
        __syncwarp();
        if (elect_one()) mbar_arrive(s_bar + B_ODONE + rnd * 8);
        TM1(3 + lr, 3);
#pragma unroll
        for (int i = 0; i < 32; i++) s[i] = ((MUFU_MASK >> (i >> 1)) & 1) ? 0.f : EXP_MAGIC;
#pragma unroll
        for (int i = 0; i < 12; i++) o[i] = 0.f;
      }
    }
  } else {
    asm volatile("setmaxnreg.dec.sync.aligned.u32 32;");
    const int w4 = __shfl_sync(0xffffffffu, warp & 3, 0);
    const int rb = blockIdx.x >> 3, ct = blockIdx.x & 7;
    if (w4 == 0) {
      int code = 0;
      bool gated = true;
#pragma unroll 1
      while (code < 32) {
        code = __shfl_sync(0xffffffffu, code, 0);
        const int job = code >> 2, p = code & 3;
        const CUtensorMap* mb = b_map(P, code);
        const CUtensorMap* ma = &P.m[p == 0 ? 1 : 0];
        const int colb = b_col(code), rowa = tok0(job & 1, rb) + (p == 0 ? 0 : (code >> 3) * S_);
#pragma unroll 1
        for (int c = 0; c < 4; c++) {
          if (code > 0) mbar_wait(s_bar + B_EMPTY + c * 8, 1);
          if (elect_one()) {
            issue_b(sbase, mb, colb, c, c);
            if (!gated) issue_a(sbase, ma, rowa, c, c);
          }
        }
        if (gated) {
          if (p == 0) {
            if (code == 0) pdl_wait();
            else { const int prev = prev_pass(code); mbar_wait(s_bar + B_EPI + (prev & 3) * 8, (prev >> 2) & 1); }
            if (elect_one()) {
              asm volatile("fence.proxy.async;" ::: "memory");
              mbar_expect(s_bar + B_RES, 8192);
              tma_load(sbase + M_STG, &P.m[job < 2 ? 7 : 0], ct * 64, tok0(job & 1, rb) + (job < 2 ? 0 : ((job >> 1) - 1) * S_), s_bar + B_RES);
            }
            cnt_wait(CNT_O + job * 4 + (rb >> 2), 32);
            TM2(12 + job, 1);
          } else {
            cnt_wait(CNT_X + job * 16 + rb, 8);
            TM2(12 + job, 3);
          }
          if (elect_one()) {
#pragma unroll
            for (int c = 0; c < 4; c++) issue_a(sbase, ma, rowa, c, c);
          }
        }
#pragma unroll 1
        for (int c = 0; c < 4; c++) {
          mbar_wait(s_bar + B_EMPTY + c * 8, 0);
          if (elect_one()) {
            issue_b(sbase, mb, colb, c, c + 4);
            issue_a(sbase, ma, rowa, c, c + 4);
          }
        }
        code = next_pass(code);
        gated = p == 0 || (code & 3) == 0;
      }
    } else if (w4 == 1) {
#pragma unroll 1
      for (int job = 0; job < 8; job++) {
        mbar_wait(s_bar + B_ODONE + (job & 1) * 8, (job >> 1) & 1);
        cnt_signal(CNT_O + job * 4 + (blockIdx.x & 3));
        if (job >= 6) continue;
        mbar_wait(s_bar + B_EPI, job & 1);
        cnt_signal(CNT_X + job * 16 + rb);
        if (pass_exists(job, 1)) {
          mbar_wait(s_bar + B_EPI + 8, job & 1);
          if (job & 2) mbar_wait(s_bar + B_EPI + 16, job & 1);
          cnt_signal(CNT_KV + job * 8 + ct);
        }
        mbar_wait(s_bar + B_EPI + 24, job & 1);
        cnt_signal(CNT_Q + (job * 4 + (rb >> 2)) * 8 + ct);
      }
    } else if (w4 == 2) {
      pdl_wait();
      load_q(sbase, 0, 0); load_kv(sbase, 0, 0); load_kv(sbase, 0, 1); load_q(sbase, 0, 1);
#pragma unroll 1
      for (int job = 0; job < 6; job++) {
        const int l = job >> 1, r = job & 1;
        mbar_wait(s_bar + B_ODONE + r * 8, l & 1);
        if (r == 0) mbar_wait(s_bar + B_FREE0, l & 1);
        cnt_wait(CNT_KV + job * 8 + ((l & 1) ? blockIdx.x >> 4 : 0), 16);
        load_kv(sbase, l + 1, r);
        cnt_wait(CNT_Q + (job * 4 + (blockIdx.x & 3)) * 8 + (blockIdx.x >> 4), 4);
        load_q(sbase, l + 1, r);
      }
    } else {
      pdl_wait();
#pragma unroll 1
      for (int job = 0; job < 6; job++) {
        float c[6];
#pragma unroll
        for (int i = 0; i < 6; i++) {
          const int p = 1 + (i >> 1);
          c[i] = __ldcg(g_colsum + ((job & 2) ? (p == 3 ? 0 : p * 512) + ct * 64 : (p == 3 ? 1536 + ct * 64 : 2048)) + (i & 1) * 32 + lane);
        }
        cnt_wait(CNT_X + job * 16 + rb, 8);
#pragma unroll
        for (int i = 0; i < 6; i++) reinterpret_cast<float*>(sm + M_CS)[i * 32 + lane] = c[i];
#pragma unroll 1
        for (int i = 0; i < 2; i++) {
          float mu, rs;
          row_stats((job >> 1) + 1, tok0(job & 1, rb) + i * 32 + lane, mu, rs);
          reinterpret_cast<float2*>(sm + M_ROW)[i * 32 + lane] = make_float2(mu, rs);
        }
        __syncwarp();
        if (elect_one()) mbar_arrive(s_bar + B_PRE);
      }
    }
    named_sync(5, 128);
    if (tid == 512) {
      unsigned old;
      asm volatile("atom.acq_rel.gpu.global.add.u32 %0, [%1], 1;" : "=r"(old) : "l"(g_cnt + CNT_DONE) : "memory");
      if (old == gridDim.x - 1)
        for (int i = 0; i < CNT_N; i++) g_cnt[i] = 0u;
    }
  }
}

typedef CUresult (*EncodeFn)(CUtensorMap*, CUtensorMapDataType, cuuint32_t, void*, const cuuint64_t*, const cuuint64_t*,
                             const cuuint32_t*, const cuuint32_t*, CUtensorMapInterleave, CUtensorMapSwizzle,
                             CUtensorMapL2promotion, CUtensorMapFloatOOBfill);

void make_map(EncodeFn enc, CUtensorMap* m, const void* p, int rows, int cols) {
  cuuint64_t dim[2] = {(cuuint64_t)cols, (cuuint64_t)rows};
  cuuint64_t str[1] = {(cuuint64_t)cols * 2};
  cuuint32_t box[2] = {64, 64};
  cuuint32_t es[2] = {1, 1};
  enc(m, CU_TENSOR_MAP_DATA_TYPE_BFLOAT16, 2, const_cast<void*>(p), dim, str, box, es, CU_TENSOR_MAP_INTERLEAVE_NONE,
      CU_TENSOR_MAP_SWIZZLE_128B, CU_TENSOR_MAP_L2_PROMOTION_L2_128B, CU_TENSOR_MAP_FLOAT_OOB_FILL_NONE);
}

template <typename... KA, typename... A>
void launch(void (*k)(KA...), int grid, int block, int smem, bool pdl, A... args) {
  cudaLaunchConfig_t cfg = {};
  cfg.gridDim = dim3(grid); cfg.blockDim = dim3(block); cfg.dynamicSmemBytes = smem; cfg.stream = cudaStreamPerThread;
  cudaLaunchAttribute at[1];
  at[0].id = cudaLaunchAttributeProgrammaticStreamSerialization;
  at[0].val.programmaticStreamSerializationAllowed = 1;
  cfg.attrs = at; cfg.numAttrs = pdl ? 1 : 0;
  cudaLaunchKernelEx(&cfg, k, KA(args)...);
}

struct HostState {
  bool init;
  const void* in[8];
  MegaParams mp;
};
HostState hs;

}

extern "C" void kernel_launch(void* const* d_in, const int* in_sizes, int n_in, void* d_out, int out_size) {
  const __nv_bfloat16* A_x = (const __nv_bfloat16*)d_in[0];
  const __nv_bfloat16* A_wqkv = (const __nv_bfloat16*)d_in[1];
  const __nv_bfloat16* A_wo = (const __nv_bfloat16*)d_in[2];
  const __nv_bfloat16* B_wq = (const __nv_bfloat16*)d_in[4];
  const __nv_bfloat16* B_wk = (const __nv_bfloat16*)d_in[5];
  const __nv_bfloat16* B_wv = (const __nv_bfloat16*)d_in[6];
  const __nv_bfloat16* B_wo = (const __nv_bfloat16*)d_in[7];
  bool same = hs.init;
  for (int i = 0; i < 8; i++) same = same && hs.in[i] == d_in[i];
  if (!same) {
    void* fn = nullptr;
    cudaDriverEntryPointQueryResult qr;
    cudaGetDriverEntryPoint("cuTensorMapEncodeTiled", &fn, cudaEnableDefault, &qr);
    EncodeFn enc = (EncodeFn)fn;
    void *px, *po, *pw;
    cudaGetSymbolAddress(&px, g_x);
    cudaGetSymbolAddress(&po, g_o);
    cudaGetSymbolAddress(&pw, g_wkv);
    make_map(enc, &hs.mp.m[7], A_x, S_, D_);
    make_map(enc, &hs.mp.m[0], px, 3 * S_, D_);
    make_map(enc, &hs.mp.m[1], po, S_, D_);
    make_map(enc, &hs.mp.m[2], A_wqkv, D_, 1536);
    make_map(enc, &hs.mp.m[3], B_wq, D_, 512);
    make_map(enc, &hs.mp.m[4], pw, D_, 32);
    make_map(enc, &hs.mp.m[5], A_wo, D_, D_);
    make_map(enc, &hs.mp.m[6], B_wo, D_, D_);
    hs.mp.x0 = A_x; hs.mp.wqkv = A_wqkv; hs.mp.wq = B_wq; hs.mp.wk = B_wk;
    cudaFuncSetAttribute(prep_kernel, cudaFuncAttributePreferredSharedMemoryCarveout, 100);
    cudaFuncSetAttribute(g1a_kernel, cudaFuncAttributeMaxDynamicSharedMemorySize, G1A_SMEM);
    cudaFuncSetAttribute(mega_kernel, cudaFuncAttributeMaxDynamicSharedMemorySize, MEGA_SMEM);
    for (int i = 0; i < 8; i++) hs.in[i] = d_in[i];
    hs.init = true;
  }
  hs.mp.out = (__nv_bfloat16*)d_out;
  launch(prep_kernel, 130, 256, 0, false, A_x, A_wqkv, B_wq, B_wk, B_wv);
  launch(g1a_kernel, 128, 288, G1A_SMEM, true, hs.mp.m[7], hs.mp.m[2]);
  launch(mega_kernel, 128, 640, MEGA_SMEM, true, hs.mp);
}
```

```cpp
#include <cuda_runtime.h>
#include <cuda_bf16.h>
#include <cuda_fp16.h>
#include <cuda.h>
#include <stdint.h>

namespace {

constexpr int S_ = 2048, D_ = 512, H_ = 32;

__device__ __align__(1024) __nv_bfloat16 g_x[3 * S_ * D_];
__device__ __align__(1024) __nv_bfloat16 g_o[S_ * D_];
__device__ __align__(1024) uint4 g_q[2 * H_ * S_ * 2];
__device__ __align__(1024) uint4 g_k[2 * H_ * S_ * 2];
__device__ __align__(1024) uint4 g_v[2 * H_ * S_ * 2];
__device__ __align__(1024) __nv_bfloat16 g_wkv[D_ * 32];
__device__ __align__(16) float2 g_stats[4 * S_ * 8];
__device__ __align__(16) float g_colsum[1536 + 512 + 64];
__device__ float g_nrm[4 * 2 * H_ * 64];
constexpr int CNT_O = 0, CNT_X = 32, CNT_KV = CNT_X + 128, CNT_Q = CNT_KV + 64, CNT_DONE = CNT_Q + 256, CNT_N = CNT_DONE + 1;
__device__ unsigned g_cnt[CNT_N];

#define TM(k, slot)
#define TM1(k, slot)
#define TM2(k, slot)
#define TM3(k, slot)
__device__ __forceinline__ uint32_t s2u(const void* p) { return (uint32_t)__cvta_generic_to_shared(p); }
__device__ __forceinline__ void mbar_init(uint32_t bar, int cnt) {
  asm volatile("mbarrier.init.shared::cta.b64 [%0], %1;" ::"r"(bar), "r"(cnt) : "memory");
}
__device__ __forceinline__ void mbar_expect(uint32_t bar, uint32_t bytes) {
  asm volatile("mbarrier.arrive.expect_tx.shared::cta.b64 _, [%0], %1;" ::"r"(bar), "r"(bytes) : "memory");
}
__device__ __forceinline__ void mbar_arrive(uint32_t bar) {
  asm volatile("mbarrier.arrive.shared::cta.b64 _, [%0];" ::"r"(bar) : "memory");
}
__device__ __forceinline__ void mbar_wait(uint32_t bar, uint32_t par) {
  uint32_t ok;
  int it = 0;
  do {
    asm volatile("{.reg .pred p; mbarrier.try_wait.parity.shared::cta.b64 p, [%1], %2; selp.u32 %0,1,0,p;}"
                 : "=r"(ok) : "r"(bar), "r"(par) : "memory");
    if (++it > (1 << 24)) __trap();
  } while (!ok);
}
__device__ __forceinline__ void mbar_wait_long(uint32_t bar, uint32_t par) {
  uint32_t ok;
  int it = 0;
  do {
    asm volatile("{.reg .pred p; mbarrier.try_wait.parity.shared::cta.b64 p, [%1], %2, 20000; selp.u32 %0,1,0,p;}"
                 : "=r"(ok) : "r"(bar), "r"(par) : "memory");
    if (++it > (1 << 22)) __trap();
  } while (!ok);
}
__device__ __forceinline__ void bulk_load(uint32_t dst, const void* src, uint32_t bytes, uint32_t bar) {
  asm volatile("cp.async.bulk.shared::cluster.global.mbarrier::complete_tx::bytes [%0], [%1], %2, [%3];"
               ::"r"(dst), "l"(src), "r"(bytes), "r"(bar) : "memory");
}
__device__ __forceinline__ void tma_load(uint32_t dst, const CUtensorMap* m, int c0, int c1, uint32_t bar) {
  asm volatile("cp.async.bulk.tensor.2d.shared::cluster.global.mbarrier::complete_tx::bytes [%0], [%1, {%3, %4}], [%2];"
               ::"r"(dst), "l"(m), "r"(bar), "r"(c0), "r"(c1) : "memory");
}
__device__ __forceinline__ bool elect_one() {
  uint32_t p;
  asm volatile("{.reg .pred q; elect.sync _|q, 0xffffffff; selp.u32 %0, 1, 0, q;}" : "=r"(p));
  return p;
}
__device__ __forceinline__ void pdl_wait() { asm volatile("griddepcontrol.wait;" ::: "memory"); }
__device__ __forceinline__ void pdl_launch() { asm volatile("griddepcontrol.launch_dependents;" ::: "memory"); }
__device__ __forceinline__ void fence_async_smem() { asm volatile("fence.proxy.async.shared::cta;" ::: "memory"); }
__device__ __forceinline__ void fence_bar_init() { asm volatile("fence.mbarrier_init.release.cluster;" ::: "memory"); }
__device__ __forceinline__ void named_sync(int id, int n) { asm volatile("bar.sync %0, %1;" ::"r"(id), "r"(n) : "memory"); }
__device__ __forceinline__ void wg_fence() { asm volatile("wgmma.fence.sync.aligned;" ::: "memory"); }
__device__ __forceinline__ void wg_commit() { asm volatile("wgmma.commit_group.sync.aligned;" ::: "memory"); }
template <int N> __device__ __forceinline__ void wg_wait() { asm volatile("wgmma.wait_group.sync.aligned %0;" ::"n"(N) : "memory"); }
template <int N> __device__ __forceinline__ void pin(float (&d)[N]) {
#pragma unroll
  for (int i = 0; i < N; i++) asm volatile("" : "+f"(d[i])::"memory");
}
template <int N> __device__ __forceinline__ void pin(uint32_t (&d)[N]) {
#pragma unroll
  for (int i = 0; i < N; i++) asm volatile("" : "+r"(d[i])::"memory");
}
__device__ __forceinline__ uint64_t mkdesc(uint32_t addr, uint32_t lbo, uint32_t sbo, uint64_t swz) {
  return (uint64_t)((addr & 0x3FFFF) >> 4) | ((uint64_t)(lbo >> 4) << 16) | ((uint64_t)(sbo >> 4) << 32) | (swz << 62);
}
__device__ __forceinline__ uint32_t pack_bf16(float lo, float hi) {
  uint32_t d; asm("cvt.rn.bf16x2.f32 %0, %1, %2;" : "=r"(d) : "f"(hi), "f"(lo)); return d;
}
__device__ __forceinline__ uint32_t pack_f16(float lo, float hi) {
  uint32_t d; asm("cvt.rn.f16x2.f32 %0, %1, %2;" : "=r"(d) : "f"(hi), "f"(lo)); return d;
}
__device__ __forceinline__ float bf_lo(uint32_t v) { return __uint_as_float(v << 16); }
__device__ __forceinline__ float bf_hi(uint32_t v) { return __uint_as_float(v & 0xffff0000u); }
__device__ __forceinline__ void stsm4(uint32_t addr, uint32_t a, uint32_t b, uint32_t c, uint32_t d) {
  asm volatile("stmatrix.sync.aligned.m8n8.x4.shared.b16 [%0], {%1,%2,%3,%4};" ::"r"(addr), "r"(a), "r"(b), "r"(c), "r"(d) : "memory");
}
__device__ __forceinline__ void ldsm4(uint32_t addr, uint32_t& a, uint32_t& b, uint32_t& c, uint32_t& d) {
  asm volatile("ldmatrix.sync.aligned.m8n8.x4.shared.b16 {%0,%1,%2,%3}, [%4];" : "=r"(a), "=r"(b), "=r"(c), "=r"(d) : "r"(addr) : "memory");
}
__device__ __forceinline__ uint32_t hadd2_bf16(uint32_t a, uint32_t b) {
  uint32_t d; asm("add.rn.bf16x2 %0, %1, %2;" : "=r"(d) : "r"(a), "r"(b)); return d;
}
__device__ __forceinline__ uint4 lds128(uint32_t addr) {
  uint4 v; asm volatile("ld.shared.v4.u32 {%0,%1,%2,%3}, [%4];" : "=r"(v.x), "=r"(v.y), "=r"(v.z), "=r"(v.w) : "r"(addr) : "memory"); return v;
}

__device__ __forceinline__ void wgmma_qk_n64(float (&d)[32], uint64_t da, uint64_t db) {
  asm volatile("wgmma.mma_async.sync.aligned.m64n64k16.f32.f16.f16 "
      "{%0,%1,%2,%3,%4,%5,%6,%7,%8,%9,%10,%11,%12,%13,%14,%15,%16,%17,%18,%19,%20,%21,%22,%23,%24,%25,%26,%27,%28,%29,%30,%31}, "
      "%32, %33, 1, 1, 1, 0, 0;"
    : "+f"(d[0]), "+f"(d[1]), "+f"(d[2]), "+f"(d[3]), "+f"(d[4]), "+f"(d[5]), "+f"(d[6]), "+f"(d[7]), "+f"(d[8]),
      "+f"(d[9]), "+f"(d[10]), "+f"(d[11]), "+f"(d[12]), "+f"(d[13]), "+f"(d[14]), "+f"(d[15]), "+f"(d[16]),
      "+f"(d[17]), "+f"(d[18]), "+f"(d[19]), "+f"(d[20]), "+f"(d[21]), "+f"(d[22]), "+f"(d[23]), "+f"(d[24]),
      "+f"(d[25]), "+f"(d[26]), "+f"(d[27]), "+f"(d[28]), "+f"(d[29]), "+f"(d[30]), "+f"(d[31])
    : "l"(da), "l"(db));
}
__device__ __forceinline__ void wgmma_pv_n24(float (&d)[12], uint32_t a0, uint32_t a1, uint32_t a2, uint32_t a3, uint64_t db) {
  asm volatile("wgmma.mma_async.sync.aligned.m64n24k16.f32.bf16.bf16 "
      "{%0,%1,%2,%3,%4,%5,%6,%7,%8,%9,%10,%11}, "
      "{%12,%13,%14,%15}, %16, 1, 1, 1, 1;"
    : "+f"(d[0]), "+f"(d[1]), "+f"(d[2]), "+f"(d[3]), "+f"(d[4]), "+f"(d[5]), "+f"(d[6]), "+f"(d[7]), "+f"(d[8]),
      "+f"(d[9]), "+f"(d[10]), "+f"(d[11])
    : "r"(a0), "r"(a1), "r"(a2), "r"(a3), "l"(db));
}
__device__ __forceinline__ void wgmma_gemm_n64(float (&d)[32], uint64_t da, uint64_t db) {
  asm volatile("wgmma.mma_async.sync.aligned.m64n64k16.f32.bf16.bf16 "
      "{%0,%1,%2,%3,%4,%5,%6,%7,%8,%9,%10,%11,%12,%13,%14,%15,%16,%17,%18,%19,%20,%21,%22,%23,%24,%25,%26,%27,%28,%29,%30,%31}, "
      "%32, %33, 1, 1, 1, 0, 1;"
    : "+f"(d[0]), "+f"(d[1]), "+f"(d[2]), "+f"(d[3]), "+f"(d[4]), "+f"(d[5]), "+f"(d[6]), "+f"(d[7]), "+f"(d[8]),
      "+f"(d[9]), "+f"(d[10]), "+f"(d[11]), "+f"(d[12]), "+f"(d[13]), "+f"(d[14]), "+f"(d[15]), "+f"(d[16]),
      "+f"(d[17]), "+f"(d[18]), "+f"(d[19]), "+f"(d[20]), "+f"(d[21]), "+f"(d[22]), "+f"(d[23]), "+f"(d[24]),
      "+f"(d[25]), "+f"(d[26]), "+f"(d[27]), "+f"(d[28]), "+f"(d[29]), "+f"(d[30]), "+f"(d[31])
    : "l"(da), "l"(db));
}
__device__ __forceinline__ void wgmma_gemm_n192(float (&d)[96], uint64_t da, uint64_t db) {
  asm volatile("wgmma.mma_async.sync.aligned.m64n192k16.f32.bf16.bf16 "
      "{%0,%1,%2,%3,%4,%5,%6,%7,%8,%9,%10,%11,%12,%13,%14,%15,%16,%17,%18,%19,%20,%21,%22,%23,%24,%25,%26,%27,%28,%29,%30,%31,%32,%33,%34,%35,%36,%37,%38,%39,%40,%41,%42,%43,%44,%45,%46,%47,%48,%49,%50,%51,%52,%53,%54,%55,%56,%57,%58,%59,%60,%61,%62,%63,%64,%65,%66,%67,%68,%69,%70,%71,%72,%73,%74,%75,%76,%77,%78,%79,%80,%81,%82,%83,%84,%85,%86,%87,%88,%89,%90,%91,%92,%93,%94,%95}, "
      "%96, %97, 1, 1, 1, 0, 1;"
    : "+f"(d[0]), "+f"(d[1]), "+f"(d[2]), "+f"(d[3]), "+f"(d[4]), "+f"(d[5]), "+f"(d[6]), "+f"(d[7]), "+f"(d[8]),
      "+f"(d[9]), "+f"(d[10]), "+f"(d[11]), "+f"(d[12]), "+f"(d[13]), "+f"(d[14]), "+f"(d[15]), "+f"(d[16]),
      "+f"(d[17]), "+f"(d[18]), "+f"(d[19]), "+f"(d[20]), "+f"(d[21]), "+f"(d[22]), "+f"(d[23]), "+f"(d[24]),
      "+f"(d[25]), "+f"(d[26]), "+f"(d[27]), "+f"(d[28]), "+f"(d[29]), "+f"(d[30]), "+f"(d[31]), "+f"(d[32]),
      "+f"(d[33]), "+f"(d[34]), "+f"(d[35]), "+f"(d[36]), "+f"(d[37]), "+f"(d[38]), "+f"(d[39]), "+f"(d[40]),
      "+f"(d[41]), "+f"(d[42]), "+f"(d[43]), "+f"(d[44]), "+f"(d[45]), "+f"(d[46]), "+f"(d[47]), "+f"(d[48]),
      "+f"(d[49]), "+f"(d[50]), "+f"(d[51]), "+f"(d[52]), "+f"(d[53]), "+f"(d[54]), "+f"(d[55]), "+f"(d[56]),
      "+f"(d[57]), "+f"(d[58]), "+f"(d[59]), "+f"(d[60]), "+f"(d[61]), "+f"(d[62]), "+f"(d[63]), "+f"(d[64]),
      "+f"(d[65]), "+f"(d[66]), "+f"(d[67]), "+f"(d[68]), "+f"(d[69]), "+f"(d[70]), "+f"(d[71]), "+f"(d[72]),
      "+f"(d[73]), "+f"(d[74]), "+f"(d[75]), "+f"(d[76]), "+f"(d[77]), "+f"(d[78]), "+f"(d[79]), "+f"(d[80]),
      "+f"(d[81]), "+f"(d[82]), "+f"(d[83]), "+f"(d[84]), "+f"(d[85]), "+f"(d[86]), "+f"(d[87]), "+f"(d[88]),
      "+f"(d[89]), "+f"(d[90]), "+f"(d[91]), "+f"(d[92]), "+f"(d[93]), "+f"(d[94]), "+f"(d[95])
    : "l"(da), "l"(db));
}

constexpr float QSCALE = 0.25f * 1.4426950408889634f;
constexpr float LN_EPS = 1e-5f;

__device__ __forceinline__ void row_stats(int layer, int row, float& mu, float& rstd) {
  const float4* p = reinterpret_cast<const float4*>(g_stats + (layer * S_ + row) * 8);
  float4 a = __ldcg(p), b = __ldcg(p + 1), c = __ldcg(p + 2), d = __ldcg(p + 3);
  float s = (a.x + a.z) + (b.x + b.z) + (c.x + c.z) + (d.x + d.z);
  float q = (a.y + a.w) + (b.y + b.w) + (c.y + c.w) + (d.y + d.w);
  mu = s * (1.f / D_);
  float var = fmaxf(q * (1.f / D_) - mu * mu, 0.f);
  rstd = rsqrtf(var + LN_EPS);
}

__global__ void __launch_bounds__(256) prep_kernel(const __nv_bfloat16* __restrict__ x, const __nv_bfloat16* __restrict__ wqkv,
                                                   const __nv_bfloat16* __restrict__ wq, const __nv_bfloat16* __restrict__ wk,
                                                   const __nv_bfloat16* __restrict__ wv) {
  TM(0, 0);
  pdl_launch();
  __shared__ float red[8][16];
  const int b = blockIdx.x, tid = threadIdx.x, lane = tid & 31, warp = tid >> 5;
  {
    const __nv_bfloat16* w; int ld, out;
    if (b < 96) { w = wqkv + b * 16; ld = 1536; out = b * 16; }
    else if (b < 128) { w = wq + (b - 96) * 16; ld = 512; out = 1536 + (b - 96) * 16; }
    else { w = (b == 128) ? wk : wv; ld = 16; out = 2048 + (b - 128) * 16; }
    const int half = tid & 1, r0 = tid >> 1;
    float acc[8];
#pragma unroll
    for (int i = 0; i < 8; i++) acc[i] = 0.f;
#pragma unroll
    for (int j = 0; j < 4; j++) {
      uint4 v = __ldg(reinterpret_cast<const uint4*>(w + (size_t)(r0 + 128 * j) * ld + half * 8));
      if (b >= 128) *reinterpret_cast<uint4*>(g_wkv + (r0 + 128 * j) * 32 + (b - 128) * 16 + half * 8) = v;
      acc[0] += bf_lo(v.x); acc[1] += bf_hi(v.x); acc[2] += bf_lo(v.y); acc[3] += bf_hi(v.y);
      acc[4] += bf_lo(v.z); acc[5] += bf_hi(v.z); acc[6] += bf_lo(v.w); acc[7] += bf_hi(v.w);
    }
#pragma unroll
    for (int i = 0; i < 8; i++) {
#pragma unroll
      for (int o = 2; o < 32; o <<= 1) acc[i] += __shfl_xor_sync(0xffffffffu, acc[i], o);
    }
    if (lane < 2) {
#pragma unroll
      for (int i = 0; i < 8; i++) red[warp][lane * 8 + i] = acc[i];
    }
    __syncthreads();
    if (tid < 16) {
      float s = 0.f;
#pragma unroll
      for (int w8 = 0; w8 < 8; w8++) s += red[w8][tid];
      g_colsum[out + tid] = s;
    }
    if (b == 129 && tid >= 32 && tid < 64) g_colsum[2048 + tid] = 0.f;
  }
  if (b < 128) {
#pragma unroll
    for (int j = 0; j < 2; j++) {
      const int row = b * 16 + warp * 2 + j;
      const uint4* p = reinterpret_cast<const uint4*>(x + (size_t)row * D_ + lane * 16);
      uint4 v0 = __ldg(p), v1 = __ldg(p + 1);
      uint32_t u[8] = {v0.x, v0.y, v0.z, v0.w, v1.x, v1.y, v1.z, v1.w};
      float s = 0.f, q = 0.f;
#pragma unroll
      for (int i = 0; i < 8; i++) {
        float a = bf_lo(u[i]), c = bf_hi(u[i]);
        s += a + c; q = fmaf(a, a, fmaf(c, c, q));
      }
      s += __shfl_xor_sync(0xffffffffu, s, 1); q += __shfl_xor_sync(0xffffffffu, q, 1);
      s += __shfl_xor_sync(0xffffffffu, s, 2); q += __shfl_xor_sync(0xffffffffu, q, 2);
      if ((lane & 3) == 0) g_stats[row * 8 + (lane >> 2)] = make_float2(s, q);
    }
  }
  TM(0, 4);
}

__device__ __forceinline__ int tok0(int r, int rb) { return (rb >> 2) * 512 + r * 256 + (rb & 3) * 64; }
__device__ __forceinline__ int key_pos(int token) {
  const int r = (token >> 8) & 1, rb = ((token >> 9) << 2) | ((token >> 6) & 3), row = token & 63;
  return (16 * r + (row >> 2)) * 64 + rb * 4 + (row & 3);
}
__device__ __forceinline__ float sq_norm16(const uint4& a, const uint4& b) {
  const uint32_t u[8] = {a.x, a.y, a.z, a.w, b.x, b.y, b.z, b.w};
  __half2 n = __hmul2(*reinterpret_cast<const __half2*>(&u[0]), *reinterpret_cast<const __half2*>(&u[0]));
#pragma unroll
  for (int i = 1; i < 8; i++) n = __hfma2(*reinterpret_cast<const __half2*>(&u[i]), *reinterpret_cast<const __half2*>(&u[i]), n);
  return __low2float(n) + __high2float(n);
}
__device__ __forceinline__ uint32_t hsub2(uint32_t a, uint32_t b) {
  uint32_t d; asm("sub.rn.f16x2 %0, %1, %2;" : "=r"(d) : "r"(a), "r"(b)); return d;
}
__device__ __forceinline__ void proj_store(uint32_t a, uint32_t ap, int type, int layer, int head, int token) {
  const uint4 v0 = lds128(a), v1 = lds128(a + 16);
  const size_t hb = (size_t)((layer & 1) * H_ + head) * (S_ * 2);
  if (type == 2) {
    uint4* dst = g_v + hb + key_pos(token);
    dst[0] = v0; dst[S_] = v1;
    return;
  }
  if (type == 0) {
    uint4* dst = g_q + hb + (token >> 3) * 16 + (token & 7);
    dst[0] = v0; dst[8] = v1;
  } else {
    uint4 d0 = v0, d1 = v1;
    if (ap) {
      const uint4 p0 = lds128(ap), p1 = lds128(ap + 16);
      d0 = make_uint4(hsub2(v0.x, p0.x), hsub2(v0.y, p0.y), hsub2(v0.z, p0.z), hsub2(v0.w, p0.w));
      d1 = make_uint4(hsub2(v1.x, p1.x), hsub2(v1.y, p1.y), hsub2(v1.z, p1.z), hsub2(v1.w, p1.w));
    }
    const int pos = key_pos(token);
    uint4* dst = g_k + hb + (pos >> 3) * 16 + (pos & 7);
    dst[0] = d0; dst[8] = d1;
  }
  const unsigned m = __reduce_max_sync(0xffffffffu, __float_as_uint(sq_norm16(v0, v1)) & 0x7fffffffu);
  if ((threadIdx.x & 31) == 0) g_nrm[((layer * 2 + type) * H_ + head) * 64 + (token >> 5)] = __uint_as_float(m);
}
template <bool F16, int N>
__device__ __forceinline__ void proj_stage(const float (&acc)[N], int j  , uint32_t addr, const float* cs,
                                           float mu0, float f0, float mu1, float f1) {
  uint32_t r[4];
#pragma unroll
  for (int e = 0; e < 2; e++) {
    const float2 c = *reinterpret_cast<const float2*>(cs + (j + e) * 8);
    const float a0 = fmaf(-mu0, c.x, acc[(j + e) * 4 + 0]) * f0, a1 = fmaf(-mu0, c.y, acc[(j + e) * 4 + 1]) * f0;
    const float a2 = fmaf(-mu1, c.x, acc[(j + e) * 4 + 2]) * f1, a3 = fmaf(-mu1, c.y, acc[(j + e) * 4 + 3]) * f1;
    r[e * 2] = F16 ? pack_f16(a0, a1) : pack_bf16(a0, a1);
    r[e * 2 + 1] = F16 ? pack_f16(a2, a3) : pack_bf16(a2, a3);
  }
  stsm4(addr + j * 16, r[0], r[1], r[2], r[3]);
}

constexpr int G1A_NS = 5, G1A_STAGE = 16384 + 3 * 8192, G1A_PITCH = 400;
constexpr int G1A_SMEM = G1A_NS * G1A_STAGE + 1024 + 192 * 4 + 128;
__global__ void __launch_bounds__(288, 1) g1a_kernel(const __grid_constant__ CUtensorMap mx, const __grid_constant__ CUtensorMap mw) {
  extern __shared__ uint8_t smem_raw[];
  const uint32_t sbase = (s2u(smem_raw) + 1023) & ~1023u;
  const uint32_t s_cs = sbase + G1A_NS * G1A_STAGE, s_bar = s_cs + 192 * 4;
  float* cs = reinterpret_cast<float*>(smem_raw + (s_cs - s2u(smem_raw)));
  const int tid = threadIdx.x, warp = tid >> 5, lane = tid & 31;
  const int nb = blockIdx.x & 7, rb = blockIdx.x >> 3;
  TM(1, 0);
  if (tid == 0) {
    for (int i = 0; i < G1A_NS; i++) { mbar_init(s_bar + i * 8, 1); mbar_init(s_bar + 40 + i * 8, 2); }
    fence_bar_init();
  }
  __syncthreads();
  if (warp == 8) {
    if (lane == 0) {
      for (int c = 0; c < 8; c++) {
        const int s = c < G1A_NS ? c : c - G1A_NS;
        const uint32_t st = sbase + s * G1A_STAGE, bar = s_bar + s * 8;
        if (c >= G1A_NS) mbar_wait(s_bar + 40 + s * 8, 0);
        mbar_expect(bar, G1A_STAGE);
        tma_load(st, &mx, c * 64, tok0(0, rb), bar);
        tma_load(st + 8192, &mx, c * 64, tok0(1, rb), bar);
        for (int j = 0; j < 3; j++) tma_load(st + 16384 + j * 8192, &mw, nb * 192 + j * 64, c * 64, bar);
      }
    }
    return;
  }
  const int wg = warp >> 2;
  float acc[96];
#pragma unroll
  for (int i = 0; i < 96; i++) acc[i] = 0.f;
  pin(acc);
#pragma unroll 1
  for (int c = 0; c < 8; c++) {
    const int s = c < G1A_NS ? c : c - G1A_NS;
    mbar_wait(s_bar + s * 8, c >= G1A_NS);
    if (c == 0) TM(1, 2);
    const uint32_t st = sbase + s * G1A_STAGE;
    const uint64_t da = mkdesc(st + wg * 8192, 16, 1024, 1), db = mkdesc(st + 16384, 8192, 1024, 1);
    wg_fence();
#pragma unroll
    for (int k = 0; k < 4; k++) wgmma_gemm_n192(acc, da + k * 2, db + k * 128);
    wg_commit();
    if (c >= 1 && c <= 3) { wg_wait<1>(); if ((tid & 127) == 0) mbar_arrive(s_bar + 40 + (c - 1) * 8); }
    if (c == 5) {
      pdl_wait();
      pdl_launch();
      if (tid < 192) cs[tid] = __ldcg(g_colsum + nb * 192 + tid);
    }
  }
  float mu0, rs0, mu1, rs1;
  const int row0 = tok0(wg, rb) + (warp & 3) * 16 + (lane >> 2);
  row_stats(0, row0, mu0, rs0); row_stats(0, row0 + 8, mu1, rs1);
  wg_wait<0>();
  pin(acc);
  TM(1, 3);
  named_sync(1, 256);
  {
    const uint32_t addr = sbase + (wg * 64 + (warp & 3) * 16 + (lane & 15)) * G1A_PITCH + (lane >> 4) * 16;
#pragma unroll
    for (int j = 0; j < 24; j += 2) {
      const int type = (nb * 12 + (j >> 1)) >> 5;
      const float sc = type == 0 ? QSCALE : 1.f;
      if (type == 2) proj_stage<false>(acc, j, addr, cs + (lane & 3) * 2, mu0, rs0, mu1, rs1);
      else proj_stage<true>(acc, j, addr, cs + (lane & 3) * 2, mu0, rs0 * sc, mu1, rs1 * sc);
    }
  }
  named_sync(1, 256);
#pragma unroll
  for (int it = 0; it < 6; it++) {
    const int item = warp + it * 8, hh = item >> 2, trow = (item & 3) * 32 + lane;
    const int hg = nb * 12 + hh;
    const uint32_t a = sbase + trow * G1A_PITCH + hh * 32;
    proj_store(a, trow >= 4 ? a - 4 * G1A_PITCH : 0u, hg >> 5, 0, hg & 31, tok0(trow >> 6, rb) + (trow & 63));
  }
  TM(1, 4);
}

constexpr uint32_t MUFU_MASK = 0xF800u;
constexpr float EXP_MAGIC = 383.0f + 0.65f / 128.0f;
constexpr uint32_t POLY_A = 0x5a835a83u, POLY_B = 0x92a192a1u, POLY_C = 0x800b800bu;
constexpr float SCORE_LIMIT = 116.f;

__device__ __forceinline__ void exp_step(const float (&s)[32], uint32_t (&p)[16], uint32_t pb) {
#pragma unroll
  for (int i = 0; i < 16; i++) {
    if ((MUFU_MASK >> i) & 1) {
      float a, b;
      asm("ex2.approx.ftz.f32 %0, %1;" : "=f"(a) : "f"(s[2 * i]));
      asm("ex2.approx.ftz.f32 %0, %1;" : "=f"(b) : "f"(s[2 * i + 1]));
      p[i] = pack_bf16(a, b);
    } else {
      uint32_t z, u, h;
      asm("prmt.b32 %0, %1, %2, 0x6521;" : "=r"(z) : "r"(__float_as_uint(s[2 * i])), "r"(__float_as_uint(s[2 * i + 1])));
      asm("fma.rn.f16x2 %0, %1, %2, %3;" : "=r"(u) : "r"(z & 0x007f007fu), "r"(POLY_A), "r"(pb));
      asm("fma.rn.f16x2 %0, %1, %1, %2;" : "=r"(h) : "r"(u), "r"(POLY_C));
      p[i] = z - h;
    }
  }
}

template <bool PV>
__device__ __forceinline__ void att_step(float (&s)[32], float (&o)[12], uint32_t (&pin_)[16], uint32_t (&pout)[16], uint64_t dq,
                                         uint64_t dk, uint64_t dv, uint32_t pb) {
  pin(s);
  if (PV) pin(pin_);
  wg_fence();
  wgmma_qk_n64(s, dq, dk);
  wg_commit();
  if (PV) {
#pragma unroll
    for (int j = 0; j < 4; j++) wgmma_pv_n24(o, pin_[4 * j], pin_[4 * j + 1], pin_[4 * j + 2], pin_[4 * j + 3], dv + j * 16);
    wg_commit();
    wg_wait<1>();
  } else {
    wg_wait<0>();
  }
  pin(s);
  exp_step(s, pout, pb);
  pin(pout);
}

constexpr int M_STAGE = 0;
constexpr int M_STG = 65536, STG_PITCH = 144;
constexpr int M_KV = 74752;
constexpr int M_Q = M_KV + 17 * 8192;
constexpr int M_CS = M_Q + 16384, M_KTAIL = M_CS + 768, M_ROW = M_KTAIL + 512, M_BAR = M_ROW + 512;
constexpr int MEGA_SMEM = M_BAR + 256;
__device__ __forceinline__ int k_unit(int j) { return j < 2 ? 7 + 2 * j : j - 2; }
__device__ __forceinline__ int v0_unit(int b) { return b == 0 ? 14 : 12 - 2 * b; }
__device__ __forceinline__ int v_stride(int b) { return b == 0 ? 1 : b + 2; }
constexpr int B_FULL = 0, B_EMPTY = 32, B_KV = 64, B_Q = 80, B_FREE0 = 96, B_ODONE = 104, B_RES = 120, B_PRE = 128,
              B_TURN = 136, B_EPI = 168;

struct MegaParams {
  CUtensorMap m[8];
  const __nv_bfloat16* x0;
  const __nv_bfloat16* wqkv; const __nv_bfloat16* wq; const __nv_bfloat16* wk;
  __nv_bfloat16* out;
};

__device__ __forceinline__ void cnt_signal(int idx) {
  if (elect_one()) asm volatile("red.release.gpu.global.add.u32 [%0], 1;" ::"l"(g_cnt + idx) : "memory");
}
__device__ __forceinline__ void cnt_wait(int idx, unsigned target) {
  unsigned v;
  int it = 0;
  while (true) {
    asm volatile("ld.acquire.gpu.global.u32 %0, [%1];" : "=r"(v) : "l"(g_cnt + idx) : "memory");
    if (v >= target) break;
    if (++it > (1 << 24)) __trap();
    __nanosleep(40);
  }
  asm volatile("fence.proxy.async.global;" ::: "memory");
}

__device__ __forceinline__ void att_fallback(const MegaParams& P, int layer, int head, int row0, __nv_bfloat16* sk, int bar_id) {
  const int t = threadIdx.x & 127, hf = t & 1;
  const __nv_bfloat16* x = layer == 0 ? P.x0 : g_x + (size_t)(layer - 1) * S_ * D_;
  const bool mqa = layer & 1;
  const __nv_bfloat16* vimg = reinterpret_cast<const __nv_bfloat16*>(g_v + (size_t)((layer & 1) * H_ + (mqa ? 0 : head)) * (S_ * 2));
  float q[16], o[16], acc[16];
  float m = -INFINITY, l = 0.f;
#pragma unroll
  for (int d = 0; d < 16; d++) { o[d] = 0.f; q[d] = 0.f; }
#pragma unroll 1
  for (int ch = -1; ch < 32; ch++) {
    const int token = ch < 0 ? row0 + (t >> 1) : ch * 64 + (t >> 1);
    const __nv_bfloat16* w = ch < 0 ? (mqa ? P.wq : P.wqkv) + head * 16 : (mqa ? P.wk : P.wqkv + 512 + head * 16);
    const int ld = mqa ? (ch < 0 ? 512 : 16) : 1536;
    float mu, rs;
    row_stats(layer, token, mu, rs);
#pragma unroll
    for (int d = 0; d < 16; d++) acc[d] = 0.f;
#pragma unroll 1
    for (int k = hf * 256; k < hf * 256 + 256; k++) {
      const unsigned short xr = __ldcg(reinterpret_cast<const unsigned short*>(x) + (size_t)token * D_ + k);
      const float xn = __bfloat162float(__float2bfloat16((__uint_as_float((uint32_t)xr << 16) - mu) * rs));
#pragma unroll
      for (int d = 0; d < 16; d++) acc[d] = fmaf(xn, __bfloat162float(w[(size_t)k * ld + d]), acc[d]);
    }
#pragma unroll
    for (int d = 0; d < 16; d++) acc[d] = __bfloat162float(__float2bfloat16(acc[d] + __shfl_xor_sync(0xffffffffu, acc[d], 1)));
    if (ch < 0) {
#pragma unroll
      for (int d = 0; d < 16; d++) q[d] = acc[d];
      continue;
    }
    named_sync(bar_id, 128);
    if (hf == 0) {
#pragma unroll
      for (int d = 0; d < 16; d++) sk[(t >> 1) * 16 + d] = __float2bfloat16(acc[d]);
    }
    named_sync(bar_id, 128);
#pragma unroll 1
    for (int j = hf * 32; j < hf * 32 + 32; j++) {
      float sc = 0.f;
#pragma unroll
      for (int d = 0; d < 16; d++) sc = fmaf(q[d], __bfloat162float(sk[j * 16 + d]), sc);
      sc *= 0.25f;
      if (sc > m || sc != sc) {
        const float a = __expf(m - sc);
        l *= a;
#pragma unroll
        for (int d = 0; d < 16; d++) o[d] *= a;
        m = sc;
      }
      const float p = __expf(sc - m);
      l += p;
      const int pos = key_pos(ch * 64 + j);
#pragma unroll
      for (int d = 0; d < 16; d++) {
        const unsigned short vr = __ldcg(reinterpret_cast<const unsigned short*>(vimg) + (d >> 3) * (S_ * 8) + pos * 8 + (d & 7));
        o[d] = fmaf(p, __uint_as_float((uint32_t)vr << 16), o[d]);
      }
    }
  }
  const float m2 = __shfl_xor_sync(0xffffffffu, m, 1), mm = fmaxf(m, m2), a = __expf(m - mm);
  l *= a; l += __shfl_xor_sync(0xffffffffu, l, 1);
  const float inv = 1.f / l;
  __nv_bfloat16* dst = g_o + (size_t)(row0 + (t >> 1)) * D_ + head * 16;
#pragma unroll
  for (int d = 0; d < 16; d++) {
    float v = o[d] * a; v += __shfl_xor_sync(0xffffffffu, v, 1);
    if ((d >> 3) == hf) dst[d] = __float2bfloat16(v * inv);
  }
}

__device__ __forceinline__ const CUtensorMap* b_map(const MegaParams& P, int code) {
  const int l = code >> 3, p = code & 3;
  return &P.m[p == 0 ? 5 + (l & 1) : ((l & 1) ? 2 : (p == 3 ? 3 : 4))];
}
__device__ __forceinline__ int b_col(int code) {
  const int p = code & 3, ct = blockIdx.x & 7;
  return p == 0 || p == 3 ? ct * 64 : ((code & 8) ? p * 512 + ct * 64 : 0);
}
__device__ __forceinline__ void issue_b(uint32_t sbase, const CUtensorMap* m, int col, int st, int c) {
  mbar_expect(sbase + M_BAR + B_FULL + st * 8, 16384);
  tma_load(sbase + M_STAGE + st * 16384 + 8192, m, col, c * 64, sbase + M_BAR + B_FULL + st * 8);
}
__device__ __forceinline__ void issue_a(uint32_t sbase, const CUtensorMap* m, int row, int st, int c) {
  tma_load(sbase + M_STAGE + st * 16384, m, c * 64, row, sbase + M_BAR + B_FULL + st * 8);
}
__device__ __forceinline__ void load_kv(uint32_t sbase, int l, int r) {
  const size_t hb = (size_t)((l & 1) * H_ + ((l & 1) ? 0 : blockIdx.x >> 2)) * 65536;
  const uint8_t* gk = reinterpret_cast<const uint8_t*>(g_k) + hb;
  const uint8_t* gv = reinterpret_cast<const uint8_t*>(g_v) + hb;
  const uint32_t bar = sbase + M_BAR + B_KV + r * 8;
  if (elect_one()) {
    mbar_expect(bar, 65536);
#pragma unroll
    for (int j = 0; j < 2; j++) {
      const int b = r * 2 + j;
      bulk_load(sbase + M_KV + k_unit(2 * b) * 8192, gk + b * 16384, 8192, bar);
      bulk_load(sbase + M_KV + v0_unit(b) * 8192, gv + b * 8192, 8192, bar);
      bulk_load(sbase + M_KV + (v0_unit(b) + v_stride(b)) * 8192, gv + 32768 + b * 8192, 8192, bar);
      bulk_load(sbase + M_KV + k_unit(2 * b + 1) * 8192, gk + b * 16384 + 8192, 8192, bar);
    }
  }
}
__device__ __forceinline__ void load_q(uint32_t sbase, int l, int r) {
  const uint32_t bar = sbase + M_BAR + B_Q + r * 8;
  if (elect_one()) {
    mbar_expect(bar, 8192);
    bulk_load(sbase + M_Q + r * 8192,
              reinterpret_cast<const uint8_t*>(g_q) + (size_t)((l & 1) * H_ + (blockIdx.x >> 2)) * 65536 + (blockIdx.x & 3) * 16384 + r * 8192,
              8192, bar);
  }
}

__device__ __forceinline__ bool pass_exists(int job, int p) {
  return p == 0 || (job < 6 && (p == 3 || (job & 2) || (p == 1 && (blockIdx.x & 7) == 0)));
}
__device__ __forceinline__ int next_pass(int code) {
  const int job = code >> 2, p = code & 3;
  if (p == 0 && pass_exists(job, 1)) return code + 1;
  if (p == 1 && pass_exists(job, 2)) return code + 1;
  if (p < 3 && pass_exists(job, 3)) return job * 4 + 3;
  return job * 4 + 4;
}
__device__ __forceinline__ int prev_pass(int code) {
  const int job = code >> 2, p = code & 3;
  if (p == 0) return job > 6 ? (job - 1) * 4 : (job - 1) * 4 + 3;
  if (p == 3 && pass_exists(job, 2)) return code - 1;
  if (p >= 2 && pass_exists(job, 1)) return job * 4 + 1;
  return job * 4;
}

__device__ __forceinline__ void proj_pass(const MegaParams& P, uint8_t* sm, uint32_t sbase, int code, int wg) {
  const uint32_t s_bar = sbase + M_BAR;
  const int prev = prev_pass(code);
  if (code > 0) mbar_wait_long(s_bar + B_TURN + (prev & 3) * 8, (prev >> 2) & 1);
  float acc[32];
#pragma unroll
  for (int i = 0; i < 32; i++) acc[i] = 0.f;
  pin(acc);
#pragma unroll 1
  for (int h = 0; h < 2; h++) {
    h = __shfl_sync(0xffffffffu, h, 0);
#pragma unroll
    for (int j = 0; j < 4; j++) {
      const uint32_t st = sbase + M_STAGE + j * 16384;
      mbar_wait_long(s_bar + B_FULL + j * 8, h);
      const uint64_t da = mkdesc(st, 16, 1024, 1), db = mkdesc(st + 8192, 8192, 1024, 1);
      wg_fence();
#pragma unroll
      for (int k = 0; k < 4; k++) wgmma_gemm_n64(acc, da + k * 2, db + k * 128);
      wg_commit();
      wg_wait<1>();
      if ((j > 0 || h == 1) && elect_one()) mbar_arrive(s_bar + B_EMPTY + ((j + 3) & 3) * 8);
    }
  }
  wg_wait<0>();
  pin(acc);
  if (elect_one()) { mbar_arrive(s_bar + B_EMPTY + 24); mbar_arrive(s_bar + B_TURN + (code & 3) * 8); }
  int t;
  asm volatile("mov.u32 %0, %%tid.x;" : "=r"(t));
  t &= 127;
  const int lane = t & 31, w4 = t >> 5;
  const int l = code >> 3, r = (code >> 2) & 1, p = code & 3;
  const int rb = blockIdx.x >> 3, ct = blockIdx.x & 7, row0 = tok0(r, rb);
  const uint32_t stg = sbase + M_STG;
  if (p == 0) {
    mbar_wait(s_bar + B_RES, r);
    const uint32_t ra = stg + (w4 * 16 + (lane & 15)) * 128;
    float s0 = 0.f, q0 = 0.f, s1 = 0.f, q1 = 0.f;
#pragma unroll
    for (int j = 0; j < 8; j += 2) {
      const uint32_t a = ra + (((j + (lane >> 4)) ^ (lane & 7)) << 4);
      uint32_t y[4];
      ldsm4(a, y[0], y[1], y[2], y[3]);
#pragma unroll
      for (int e = 0; e < 4; e++) {
        y[e] = hadd2_bf16(y[e], pack_bf16(acc[4 * j + 2 * e], acc[4 * j + 2 * e + 1]));
        const float lo = bf_lo(y[e]), hi = bf_hi(y[e]);
        if (e & 1) { s1 += lo + hi; q1 = fmaf(lo, lo, fmaf(hi, hi, q1)); }
        else { s0 += lo + hi; q0 = fmaf(lo, lo, fmaf(hi, hi, q0)); }
      }
      stsm4(a, y[0], y[1], y[2], y[3]);
    }
    __syncwarp();
    __nv_bfloat16* xout = (l == 3 ? P.out : g_x + (size_t)l * S_ * D_) + (size_t)(row0 + w4 * 16 + (lane >> 3)) * D_ + ct * 64 + (lane & 7) * 8;
#pragma unroll
    for (int i = 0; i < 4; i++) {
      const int rr = i * 4 + (lane >> 3);
      *reinterpret_cast<uint4*>(xout + (size_t)i * 4 * D_) = lds128(stg + (w4 * 16 + rr) * 128 + (((lane & 7) ^ (rr & 7)) << 4));
    }
    if (l < 3) {
#pragma unroll
      for (int o = 1; o < 4; o <<= 1) {
        s0 += __shfl_xor_sync(0xffffffffu, s0, o); q0 += __shfl_xor_sync(0xffffffffu, q0, o);
        s1 += __shfl_xor_sync(0xffffffffu, s1, o); q1 += __shfl_xor_sync(0xffffffffu, q1, o);
      }
      if ((lane & 3) == 0) {
        float2* st = g_stats + ((l + 1) * S_ + row0 + w4 * 16 + (lane >> 2)) * 8 + ct;
        st[0] = make_float2(s0, q0); st[64] = make_float2(s1, q1);
      }
    }
  } else {
    const bool kv = !(l & 1) && p == 1;
    const int type = p == 3 ? 0 : p;
    mbar_wait(s_bar + B_PRE, r);
    mbar_wait(s_bar + B_EPI + (prev & 3) * 8, (prev >> 2) & 1);
    const float2 st0 = reinterpret_cast<const float2*>(sm + M_ROW)[w4 * 16 + (lane >> 2)];
    const float2 st1 = reinterpret_cast<const float2*>(sm + M_ROW)[w4 * 16 + (lane >> 2) + 8];
    const float* cs = reinterpret_cast<const float*>(sm + M_CS) + (p - 1) * 64 + (lane & 3) * 2;
    const uint32_t saddr = stg + (w4 * 16 + (lane & 15)) * STG_PITCH + (lane >> 4) * 16;
    if (kv) {
      proj_stage<true>(acc, 0, saddr, cs, st0.x, st0.y, st1.x, st1.y);
      proj_stage<false>(acc, 2, saddr, cs, st0.x, st0.y, st1.x, st1.y);
    } else if (type == 2) {
#pragma unroll
      for (int j = 0; j < 8; j += 2) proj_stage<false>(acc, j, saddr, cs, st0.x, st0.y, st1.x, st1.y);
    } else {
      const float sc = type == 0 ? QSCALE : 1.f, f0 = st0.y * sc, f1 = st1.y * sc;
#pragma unroll
      for (int j = 0; j < 8; j += 2) proj_stage<true>(acc, j, saddr, cs, st0.x, f0, st1.x, f1);
    }
    named_sync(wg + 1, 128);
    const int row = t & 63;
#pragma unroll
    for (int i = 0; i < 2; i++) {
      if (kv && i == 1) break;
      const int hh = 2 * i + (t >> 6);
      const uint32_t a = stg + row * STG_PITCH + hh * 32;
      const uint32_t ap = row >= 4 ? a - 4 * STG_PITCH : (r ? sbase + M_KTAIL + row * 128 + hh * 32 : 0u);
      proj_store(a, ap, kv ? 1 + hh : type, l + 1, kv ? 0 : ct * 4 + hh, row0 + row);
    }
    if (p == 1 && r == 0 && t < 32)
      *reinterpret_cast<uint4*>(sm + M_KTAIL + t * 16) = lds128(stg + (60 + (t >> 3)) * STG_PITCH + (t & 7) * 16);
  }
  __syncwarp();
  if (lane == 0) mbar_arrive(s_bar + B_EPI + p * 8);
}

__global__ void __launch_bounds__(640, 1) mega_kernel(const __grid_constant__ MegaParams P) {
  extern __shared__ __align__(1024) uint8_t sm[];
  const uint32_t sbase = s2u(sm);
  if (sbase & 1023) __trap();
  const uint32_t s_bar = sbase + M_BAR;
  const int tid = threadIdx.x, warp = tid >> 5, lane = tid & 31;
  TM(2, 0);
  if (tid == 0) {
    for (int i = 0; i < 4; i++) {
      mbar_init(s_bar + B_FULL + i * 8, 1); mbar_init(s_bar + B_EMPTY + i * 8, 4);
      mbar_init(s_bar + B_TURN + i * 8, 4); mbar_init(s_bar + B_EPI + i * 8, 4);
    }
    for (int i = 0; i < 2; i++) { mbar_init(s_bar + B_KV + i * 8, 1); mbar_init(s_bar + B_Q + i * 8, 1); mbar_init(s_bar + B_ODONE + i * 8, 16); }
    mbar_init(s_bar + B_FREE0, 16);
    mbar_init(s_bar + B_RES, 1);
    mbar_init(s_bar + B_PRE, 1);
    fence_bar_init();
  }
  if (tid < 512) *reinterpret_cast<uint4*>(sm + M_KV + 16 * 8192 + tid * 16) = make_uint4(0x3f803f80u, 0x3f803f80u, 0x3f803f80u, 0x3f803f80u);
  fence_async_smem();
  __syncthreads();
  const int wg = __shfl_sync(0xffffffffu, warp >> 2, 0);

  if (wg < 4) {
    asm volatile("setmaxnreg.inc.sync.aligned.u32 112;");
    pdl_wait();
    const int head = blockIdx.x >> 2, quarter = blockIdx.x & 3;
    uint32_t pb = POLY_B;
    asm volatile("" : "+r"(pb));
    float s[32], o[12];
#pragma unroll
    for (int i = 0; i < 32; i++) s[i] = ((MUFU_MASK >> (i >> 1)) & 1) ? 0.f : EXP_MAGIC;
#pragma unroll
    for (int i = 0; i < 12; i++) o[i] = 0.f;
#pragma unroll 1
    for (int it = 0; it <= 32; it++) {
      it = __shfl_sync(0xffffffffu, it, 0);
      const int lr = it >> 2, b = it & 3, rnd = lr & 1, layer = lr >> 1;
      const uint32_t par = layer & 1;
      {
        const int job = lr - 1, p = (wg - job) & 3;
        if (job >= 0 && b == ((p + 1) >> 1) && pass_exists(job, p)) {
          TM3(24 + job * 4 + p, 0);
          proj_pass(P, sm, sbase, job * 4 + p, wg);
          TM3(24 + job * 4 + p, 1);
        }
      }
      if (it == 32) break;
      if (b == 0) mbar_wait_long(s_bar + B_Q + rnd * 8, par);
      if (b == 2) TM1(3 + lr, 1);
      mbar_wait_long(s_bar + B_KV + (b >> 1) * 8, par);
      if (b == 0) TM1(3 + lr, 0);
      if (b == 2) TM1(3 + lr, 2);
      {
        uint32_t p0[16], p1[16];
        const uint64_t dq = mkdesc(sbase + M_Q + rnd * 8192 + wg * 2048, 128, 256, 0);
        const uint64_t dk0 = mkdesc(sbase + M_KV + k_unit(2 * b) * 8192, 128, 256, 0);
        const uint64_t dk1 = mkdesc(sbase + M_KV + k_unit(2 * b + 1) * 8192, 128, 256, 0);
        const uint64_t dv = mkdesc(sbase + M_KV + v0_unit(b) * 8192, 128, v_stride(b) * 8192, 0);
        pin(o);
        att_step<false>(s, o, p1, p0, dq, dk0, dv, pb);
        att_step<true>(s, o, p0, p1, dq, dk0 + 128, dv, pb);
        att_step<true>(s, o, p1, p0, dq, dk0 + 256, dv + 64, pb);
        att_step<true>(s, o, p0, p1, dq, dk0 + 384, dv + 128, pb);
        att_step<true>(s, o, p1, p0, dq, dk1, dv + 192, pb);
        att_step<true>(s, o, p0, p1, dq, dk1 + 128, dv + 256, pb);
        att_step<true>(s, o, p1, p0, dq, dk1 + 256, dv + 320, pb);
        att_step<true>(s, o, p0, p1, dq, dk1 + 384, dv + 384, pb);
        pin(p1);
        wg_fence();
#pragma unroll
        for (int j = 0; j < 4; j++) wgmma_pv_n24(o, p1[4 * j], p1[4 * j + 1], p1[4 * j + 2], p1[4 * j + 3], dv + 448 + j * 16);
        wg_commit();
        wg_wait<0>();
        pin(o); pin(s);
      }
      if (b == 1 && rnd == 1 && elect_one()) mbar_arrive(s_bar + B_FREE0);
      if (b == 3) {
        int t;
        asm volatile("mov.u32 %0, %%tid.x;" : "=r"(t));
        const int ln = t & 31;
        const int row0 = quarter * 512 + rnd * 256 + wg * 64;
        const float* nq = g_nrm + (layer * 2 * H_ + head) * 64 + (row0 >> 5);
        const float* nk = g_nrm + ((layer * 2 + 1) * H_ + (par ? 0 : head)) * 64;
        const unsigned qn = max(__float_as_uint(__ldcg(nq)), __float_as_uint(__ldcg(nq + 1)));
        const unsigned kn = __reduce_max_sync(0xffffffffu, max(__float_as_uint(__ldcg(nk + ln)), __float_as_uint(__ldcg(nk + 32 + ln))));
        const float l0 = o[8], l1 = o[10];
        float mx = 0.f;
#pragma unroll
        for (int i = 0; i < 8; i++) mx += fabsf(o[i]);
        const float i0 = __fdividef(1.f, l0), i1 = __fdividef(1.f, l1);
        __nv_bfloat16* dst = g_o + (size_t)(row0 + ((t >> 5) & 3) * 16 + (ln >> 2)) * D_ + head * 16 + (ln & 3) * 2;
        *reinterpret_cast<uint32_t*>(dst) = pack_bf16(o[0] * i0, o[1] * i0);
        *reinterpret_cast<uint32_t*>(dst + 8) = pack_bf16(o[4] * i0, o[5] * i0);
        *reinterpret_cast<uint32_t*>(dst + 8 * D_) = pack_bf16(o[2] * i1, o[3] * i1);
        *reinterpret_cast<uint32_t*>(dst + 8 * D_ + 8) = pack_bf16(o[6] * i1, o[7] * i1);
        const bool ok = __uint_as_float(qn) * __uint_as_float(kn) <= SCORE_LIMIT * SCORE_LIMIT && l0 >= 1e-18f && l0 <= 1e37f &&
                        l1 >= 1e-18f && l1 <= 1e37f && mx <= 3e38f;
        uint32_t bad;
        asm volatile("{.reg .pred p, q; setp.eq.u32 p, %1, 0; barrier.red.or.pred.aligned q, %2, 128, p; selp.u32 %0, 1, 0, q;}"
                     : "=r"(bad) : "r"((uint32_t)ok), "r"(wg + 1) : "memory");
        if (bad) {
          att_fallback(P, layer, head, row0, reinterpret_cast<__nv_bfloat16*>(sm + M_Q + rnd * 8192 + wg * 2048), wg + 1);
          fence_async_smem();
        }
        __syncwarp();
        if (elect_one()) mbar_arrive(s_bar + B_ODONE + rnd * 8);
        TM1(3 + lr, 3);
#pragma unroll
        for (int i = 0; i < 32; i++) s[i] = ((MUFU_MASK >> (i >> 1)) & 1) ? 0.f : EXP_MAGIC;
#pragma unroll
        for (int i = 0; i < 12; i++) o[i] = 0.f;
      }
    }
  } else {
    asm volatile("setmaxnreg.dec.sync.aligned.u32 32;");
    const int w4 = __shfl_sync(0xffffffffu, warp & 3, 0);
    const int rb = blockIdx.x >> 3, ct = blockIdx.x & 7;
    if (w4 == 0) {
      int code = 0;
      bool gated = true;
#pragma unroll 1
      while (code < 32) {
        code = __shfl_sync(0xffffffffu, code, 0);
        const int job = code >> 2, p = code & 3;
        const CUtensorMap* mb = b_map(P, code);
        const CUtensorMap* ma = &P.m[p == 0 ? 1 : 0];
        const int colb = b_col(code), rowa = tok0(job & 1, rb) + (p == 0 ? 0 : (code >> 3) * S_);
#pragma unroll 1
        for (int c = 0; c < 4; c++) {
          if (code > 0) mbar_wait_long(s_bar + B_EMPTY + c * 8, 1);
          if (elect_one()) {
            issue_b(sbase, mb, colb, c, c);
            if (!gated) issue_a(sbase, ma, rowa, c, c);
          }
        }
        if (gated) {
          if (p == 0) {
            if (code == 0) pdl_wait();
            else { const int prev = prev_pass(code); mbar_wait_long(s_bar + B_EPI + (prev & 3) * 8, (prev >> 2) & 1); }
            if (elect_one()) {
              asm volatile("fence.proxy.async;" ::: "memory");
              mbar_expect(s_bar + B_RES, 8192);
              tma_load(sbase + M_STG, &P.m[job < 2 ? 7 : 0], ct * 64, tok0(job & 1, rb) + (job < 2 ? 0 : ((job >> 1) - 1) * S_), s_bar + B_RES);
            }
            mbar_wait_long(s_bar + B_ODONE + (job & 1) * 8, (job >> 1) & 1);
            cnt_wait(CNT_O + job * 4 + (rb >> 2), 32);
            TM2(12 + job, 1);
          } else {
            mbar_wait_long(s_bar + B_EPI, job & 1);
            cnt_wait(CNT_X + job * 16 + rb, 8);
            TM2(12 + job, 3);
          }
          if (elect_one()) {
#pragma unroll
            for (int c = 0; c < 4; c++) issue_a(sbase, ma, rowa, c, c);
          }
        }
#pragma unroll 1
        for (int c = 0; c < 4; c++) {
          mbar_wait_long(s_bar + B_EMPTY + c * 8, 0);
          if (elect_one()) {
            issue_b(sbase, mb, colb, c, c + 4);
            issue_a(sbase, ma, rowa, c, c + 4);
          }
        }
        code = next_pass(code);
        gated = p == 0 || (code & 3) == 0;
      }
    } else if (w4 == 1) {
#pragma unroll 1
      for (int job = 0; job < 8; job++) {
        mbar_wait_long(s_bar + B_ODONE + (job & 1) * 8, (job >> 1) & 1);
        cnt_signal(CNT_O + job * 4 + (blockIdx.x & 3));
        if (job >= 6) continue;
        mbar_wait_long(s_bar + B_EPI, job & 1);
        cnt_signal(CNT_X + job * 16 + rb);
        if (pass_exists(job, 1)) {
          mbar_wait_long(s_bar + B_EPI + 8, job & 1);
          if (job & 2) mbar_wait_long(s_bar + B_EPI + 16, job & 1);
          cnt_signal(CNT_KV + job * 8 + ct);
        }
        mbar_wait_long(s_bar + B_EPI + 24, job & 1);
        cnt_signal(CNT_Q + (job * 4 + (rb >> 2)) * 8 + ct);
      }
    } else if (w4 == 2) {
      pdl_wait();
      load_q(sbase, 0, 0); load_kv(sbase, 0, 0); load_kv(sbase, 0, 1); load_q(sbase, 0, 1);
#pragma unroll 1
      for (int job = 0; job < 6; job++) {
        const int l = job >> 1, r = job & 1;
        mbar_wait_long(s_bar + B_ODONE + r * 8, l & 1);
        if (r == 0) mbar_wait_long(s_bar + B_FREE0, l & 1);
        mbar_wait_long(s_bar + B_TURN, job & 1);
        cnt_wait(CNT_KV + job * 8 + ((l & 1) ? blockIdx.x >> 4 : 0), 16);
        load_kv(sbase, l + 1, r);
        cnt_wait(CNT_Q + (job * 4 + (blockIdx.x & 3)) * 8 + (blockIdx.x >> 4), 4);
        load_q(sbase, l + 1, r);
      }
    } else {
      pdl_wait();
#pragma unroll 1
      for (int job = 0; job < 6; job++) {
        float c[6];
#pragma unroll
        for (int i = 0; i < 6; i++) {
          const int p = 1 + (i >> 1);
          c[i] = __ldcg(g_colsum + ((job & 2) ? (p == 3 ? 0 : p * 512) + ct * 64 : (p == 3 ? 1536 + ct * 64 : 2048)) + (i & 1) * 32 + lane);
        }
        mbar_wait_long(s_bar + B_EPI, job & 1);
        cnt_wait(CNT_X + job * 16 + rb, 8);
#pragma unroll
        for (int i = 0; i < 6; i++) reinterpret_cast<float*>(sm + M_CS)[i * 32 + lane] = c[i];
#pragma unroll 1
        for (int i = 0; i < 2; i++) {
          float mu, rs;
          row_stats((job >> 1) + 1, tok0(job & 1, rb) + i * 32 + lane, mu, rs);
          reinterpret_cast<float2*>(sm + M_ROW)[i * 32 + lane] = make_float2(mu, rs);
        }
        __syncwarp();
        if (elect_one()) mbar_arrive(s_bar + B_PRE);
      }
    }
    named_sync(5, 128);
    if (tid == 512) {
      unsigned old;
      asm volatile("atom.acq_rel.gpu.global.add.u32 %0, [%1], 1;" : "=r"(old) : "l"(g_cnt + CNT_DONE) : "memory");
      if (old == gridDim.x - 1)
        for (int i = 0; i < CNT_N; i++) g_cnt[i] = 0u;
    }
  }
}

typedef CUresult (*EncodeFn)(CUtensorMap*, CUtensorMapDataType, cuuint32_t, void*, const cuuint64_t*, const cuuint64_t*,
                             const cuuint32_t*, const cuuint32_t*, CUtensorMapInterleave, CUtensorMapSwizzle,
                             CUtensorMapL2promotion, CUtensorMapFloatOOBfill);

void make_map(EncodeFn enc, CUtensorMap* m, const void* p, int rows, int cols) {
  cuuint64_t dim[2] = {(cuuint64_t)cols, (cuuint64_t)rows};
  cuuint64_t str[1] = {(cuuint64_t)cols * 2};
  cuuint32_t box[2] = {64, 64};
  cuuint32_t es[2] = {1, 1};
  enc(m, CU_TENSOR_MAP_DATA_TYPE_BFLOAT16, 2, const_cast<void*>(p), dim, str, box, es, CU_TENSOR_MAP_INTERLEAVE_NONE,
      CU_TENSOR_MAP_SWIZZLE_128B, CU_TENSOR_MAP_L2_PROMOTION_L2_128B, CU_TENSOR_MAP_FLOAT_OOB_FILL_NONE);
}

template <typename... KA, typename... A>
void launch(void (*k)(KA...), int grid, int block, int smem, bool pdl, A... args) {
  cudaLaunchConfig_t cfg = {};
  cfg.gridDim = dim3(grid); cfg.blockDim = dim3(block); cfg.dynamicSmemBytes = smem; cfg.stream = cudaStreamPerThread;
  cudaLaunchAttribute at[1];
  at[0].id = cudaLaunchAttributeProgrammaticStreamSerialization;
  at[0].val.programmaticStreamSerializationAllowed = 1;
  cfg.attrs = at; cfg.numAttrs = pdl ? 1 : 0;
  cudaLaunchKernelEx(&cfg, k, KA(args)...);
}

struct HostState {
  bool init;
  const void* in[8];
  MegaParams mp;
};
HostState hs;

}

extern "C" void kernel_launch(void* const* d_in, const int* in_sizes, int n_in, void* d_out, int out_size) {
  const __nv_bfloat16* A_x = (const __nv_bfloat16*)d_in[0];
  const __nv_bfloat16* A_wqkv = (const __nv_bfloat16*)d_in[1];
  const __nv_bfloat16* A_wo = (const __nv_bfloat16*)d_in[2];
  const __nv_bfloat16* B_wq = (const __nv_bfloat16*)d_in[4];
  const __nv_bfloat16* B_wk = (const __nv_bfloat16*)d_in[5];
  const __nv_bfloat16* B_wv = (const __nv_bfloat16*)d_in[6];
  const __nv_bfloat16* B_wo = (const __nv_bfloat16*)d_in[7];
  bool same = hs.init;
  for (int i = 0; i < 8; i++) same = same && hs.in[i] == d_in[i];
  if (!same) {
    void* fn = nullptr;
    cudaDriverEntryPointQueryResult qr;
    cudaGetDriverEntryPoint("cuTensorMapEncodeTiled", &fn, cudaEnableDefault, &qr);
    EncodeFn enc = (EncodeFn)fn;
    void *px, *po, *pw;
    cudaGetSymbolAddress(&px, g_x);
    cudaGetSymbolAddress(&po, g_o);
    cudaGetSymbolAddress(&pw, g_wkv);
    make_map(enc, &hs.mp.m[7], A_x, S_, D_);
    make_map(enc, &hs.mp.m[0], px, 3 * S_, D_);
    make_map(enc, &hs.mp.m[1], po, S_, D_);
    make_map(enc, &hs.mp.m[2], A_wqkv, D_, 1536);
    make_map(enc, &hs.mp.m[3], B_wq, D_, 512);
    make_map(enc, &hs.mp.m[4], pw, D_, 32);
    make_map(enc, &hs.mp.m[5], A_wo, D_, D_);
    make_map(enc, &hs.mp.m[6], B_wo, D_, D_);
    hs.mp.x0 = A_x; hs.mp.wqkv = A_wqkv; hs.mp.wq = B_wq; hs.mp.wk = B_wk;
    cudaFuncSetAttribute(prep_kernel, cudaFuncAttributePreferredSharedMemoryCarveout, 100);
    cudaFuncSetAttribute(g1a_kernel, cudaFuncAttributeMaxDynamicSharedMemorySize, G1A_SMEM);
    cudaFuncSetAttribute(mega_kernel, cudaFuncAttributeMaxDynamicSharedMemorySize, MEGA_SMEM);
    for (int i = 0; i < 8; i++) hs.in[i] = d_in[i];
    hs.init = true;
  }
  hs.mp.out = (__nv_bfloat16*)d_out;
  launch(prep_kernel, 130, 256, 0, false, A_x, A_wqkv, B_wq, B_wk, B_wv);
  launch(g1a_kernel, 128, 288, G1A_SMEM, true, hs.mp.m[7], hs.mp.m[2]);
  launch(mega_kernel, 128, 640, MEGA_SMEM, true, hs.mp);
}
```

```cpp
#include <cuda_runtime.h>
#include <cuda_bf16.h>
#include <cuda_fp16.h>
#include <cuda.h>
#include <stdint.h>

namespace {

constexpr int S_ = 2048, D_ = 512, H_ = 32;

__device__ __align__(1024) __nv_bfloat16 g_x[3 * S_ * D_];
__device__ __align__(1024) __nv_bfloat16 g_o[S_ * D_];
__device__ __align__(1024) uint4 g_q[2 * H_ * S_ * 2];
__device__ __align__(1024) uint4 g_k[2 * H_ * S_ * 2];
__device__ __align__(1024) uint4 g_v[2 * H_ * S_ * 2];
__device__ __align__(1024) __nv_bfloat16 g_wkv[D_ * 32];
__device__ __align__(16) float2 g_stats[4 * S_ * 8];
__device__ __align__(16) float g_colsum[1536 + 512 + 64];
__device__ float g_nrm[4 * 2 * H_ * 64];
constexpr int CNT_O = 0, CNT_X = 32, CNT_KV = CNT_X + 128, CNT_Q = CNT_KV + 64, CNT_DONE = CNT_Q + 256, CNT_N = CNT_DONE + 1;
__device__ unsigned g_cnt[CNT_N];

#define TM(k, slot)
#define TM1(k, slot)
#define TM2(k, slot)
#define TM3(k, slot)
__device__ __forceinline__ uint32_t s2u(const void* p) { return (uint32_t)__cvta_generic_to_shared(p); }
__device__ __forceinline__ void mbar_init(uint32_t bar, int cnt) {
  asm volatile("mbarrier.init.shared::cta.b64 [%0], %1;" ::"r"(bar), "r"(cnt) : "memory");
}
__device__ __forceinline__ void mbar_expect(uint32_t bar, uint32_t bytes) {
  asm volatile("mbarrier.arrive.expect_tx.shared::cta.b64 _, [%0], %1;" ::"r"(bar), "r"(bytes) : "memory");
}
__device__ __forceinline__ void mbar_arrive(uint32_t bar) {
  asm volatile("mbarrier.arrive.shared::cta.b64 _, [%0];" ::"r"(bar) : "memory");
}
__device__ __forceinline__ void mbar_wait(uint32_t bar, uint32_t par) {
  uint32_t ok;
  int it = 0;
  do {
    asm volatile("{.reg .pred p; mbarrier.try_wait.parity.shared::cta.b64 p, [%1], %2; selp.u32 %0,1,0,p;}"
                 : "=r"(ok) : "r"(bar), "r"(par) : "memory");
    if (++it > (1 << 24)) __trap();
  } while (!ok);
}
__device__ __forceinline__ void mbar_wait_long(uint32_t bar, uint32_t par) {
  uint32_t ok;
  int it = 0;
  do {
    asm volatile("{.reg .pred p; mbarrier.try_wait.parity.shared::cta.b64 p, [%1], %2, 20000; selp.u32 %0,1,0,p;}"
                 : "=r"(ok) : "r"(bar), "r"(par) : "memory");
    if (++it > (1 << 22)) __trap();
  } while (!ok);
}
__device__ __forceinline__ void bulk_load(uint32_t dst, const void* src, uint32_t bytes, uint32_t bar) {
  asm volatile("cp.async.bulk.shared::cluster.global.mbarrier::complete_tx::bytes [%0], [%1], %2, [%3];"
               ::"r"(dst), "l"(src), "r"(bytes), "r"(bar) : "memory");
}
__device__ __forceinline__ void tma_load(uint32_t dst, const CUtensorMap* m, int c0, int c1, uint32_t bar) {
  asm volatile("cp.async.bulk.tensor.2d.shared::cluster.global.mbarrier::complete_tx::bytes [%0], [%1, {%3, %4}], [%2];"
               ::"r"(dst), "l"(m), "r"(bar), "r"(c0), "r"(c1) : "memory");
}
__device__ __forceinline__ bool elect_one() {
  uint32_t p;
  asm volatile("{.reg .pred q; elect.sync _|q, 0xffffffff; selp.u32 %0, 1, 0, q;}" : "=r"(p));
  return p;
}
__device__ __forceinline__ void pdl_wait() { asm volatile("griddepcontrol.wait;" ::: "memory"); }
__device__ __forceinline__ void pdl_launch() { asm volatile("griddepcontrol.launch_dependents;" ::: "memory"); }
__device__ __forceinline__ void fence_async_smem() { asm volatile("fence.proxy.async.shared::cta;" ::: "memory"); }
__device__ __forceinline__ void fence_bar_init() { asm volatile("fence.mbarrier_init.release.cluster;" ::: "memory"); }
__device__ __forceinline__ void named_sync(int id, int n) { asm volatile("bar.sync %0, %1;" ::"r"(id), "r"(n) : "memory"); }
__device__ __forceinline__ void wg_fence() { asm volatile("wgmma.fence.sync.aligned;" ::: "memory"); }
__device__ __forceinline__ void wg_commit() { asm volatile("wgmma.commit_group.sync.aligned;" ::: "memory"); }
template <int N> __device__ __forceinline__ void wg_wait() { asm volatile("wgmma.wait_group.sync.aligned %0;" ::"n"(N) : "memory"); }
template <int N> __device__ __forceinline__ void pin(float (&d)[N]) {
#pragma unroll
  for (int i = 0; i < N; i++) asm volatile("" : "+f"(d[i])::"memory");
}
template <int N> __device__ __forceinline__ void pin(uint32_t (&d)[N]) {
#pragma unroll
  for (int i = 0; i < N; i++) asm volatile("" : "+r"(d[i])::"memory");
}
__device__ __forceinline__ uint64_t mkdesc(uint32_t addr, uint32_t lbo, uint32_t sbo, uint64_t swz) {
  return (uint64_t)((addr & 0x3FFFF) >> 4) | ((uint64_t)(lbo >> 4) << 16) | ((uint64_t)(sbo >> 4) << 32) | (swz << 62);
}
__device__ __forceinline__ uint32_t pack_bf16(float lo, float hi) {
  uint32_t d; asm("cvt.rn.bf16x2.f32 %0, %1, %2;" : "=r"(d) : "f"(hi), "f"(lo)); return d;
}
__device__ __forceinline__ uint32_t pack_f16(float lo, float hi) {
  uint32_t d; asm("cvt.rn.f16x2.f32 %0, %1, %2;" : "=r"(d) : "f"(hi), "f"(lo)); return d;
}
__device__ __forceinline__ float bf_lo(uint32_t v) { return __uint_as_float(v << 16); }
__device__ __forceinline__ float bf_hi(uint32_t v) { return __uint_as_float(v & 0xffff0000u); }
__device__ __forceinline__ void stsm4(uint32_t addr, uint32_t a, uint32_t b, uint32_t c, uint32_t d) {
  asm volatile("stmatrix.sync.aligned.m8n8.x4.shared.b16 [%0], {%1,%2,%3,%4};" ::"r"(addr), "r"(a), "r"(b), "r"(c), "r"(d) : "memory");
}
__device__ __forceinline__ void ldsm4(uint32_t addr, uint32_t& a, uint32_t& b, uint32_t& c, uint32_t& d) {
  asm volatile("ldmatrix.sync.aligned.m8n8.x4.shared.b16 {%0,%1,%2,%3}, [%4];" : "=r"(a), "=r"(b), "=r"(c), "=r"(d) : "r"(addr) : "memory");
}
__device__ __forceinline__ uint32_t hadd2_bf16(uint32_t a, uint32_t b) {
  uint32_t d; asm("add.rn.bf16x2 %0, %1, %2;" : "=r"(d) : "r"(a), "r"(b)); return d;
}
__device__ __forceinline__ uint4 lds128(uint32_t addr) {
  uint4 v; asm volatile("ld.shared.v4.u32 {%0,%1,%2,%3}, [%4];" : "=r"(v.x), "=r"(v.y), "=r"(v.z), "=r"(v.w) : "r"(addr) : "memory"); return v;
}

__device__ __forceinline__ void wgmma_qk_n64(float (&d)[32], uint64_t da, uint64_t db) {
  asm volatile("wgmma.mma_async.sync.aligned.m64n64k16.f32.f16.f16 "
      "{%0,%1,%2,%3,%4,%5,%6,%7,%8,%9,%10,%11,%12,%13,%14,%15,%16,%17,%18,%19,%20,%21,%22,%23,%24,%25,%26,%27,%28,%29,%30,%31}, "
      "%32, %33, 1, 1, 1, 0, 0;"
    : "+f"(d[0]), "+f"(d[1]), "+f"(d[2]), "+f"(d[3]), "+f"(d[4]), "+f"(d[5]), "+f"(d[6]), "+f"(d[7]), "+f"(d[8]),
      "+f"(d[9]), "+f"(d[10]), "+f"(d[11]), "+f"(d[12]), "+f"(d[13]), "+f"(d[14]), "+f"(d[15]), "+f"(d[16]),
      "+f"(d[17]), "+f"(d[18]), "+f"(d[19]), "+f"(d[20]), "+f"(d[21]), "+f"(d[22]), "+f"(d[23]), "+f"(d[24]),
      "+f"(d[25]), "+f"(d[26]), "+f"(d[27]), "+f"(d[28]), "+f"(d[29]), "+f"(d[30]), "+f"(d[31])
    : "l"(da), "l"(db));
}
__device__ __forceinline__ void wgmma_pv_n24(float (&d)[12], uint32_t a0, uint32_t a1, uint32_t a2, uint32_t a3, uint64_t db) {
  asm volatile("wgmma.mma_async.sync.aligned.m64n24k16.f32.bf16.bf16 "
      "{%0,%1,%2,%3,%4,%5,%6,%7,%8,%9,%10,%11}, "
      "{%12,%13,%14,%15}, %16, 1, 1, 1, 1;"
    : "+f"(d[0]), "+f"(d[1]), "+f"(d[2]), "+f"(d[3]), "+f"(d[4]), "+f"(d[5]), "+f"(d[6]), "+f"(d[7]), "+f"(d[8]),
      "+f"(d[9]), "+f"(d[10]), "+f"(d[11])
    : "r"(a0), "r"(a1), "r"(a2), "r"(a3), "l"(db));
}
__device__ __forceinline__ void wgmma_gemm_n64(float (&d)[32], uint64_t da, uint64_t db) {
  asm volatile("wgmma.mma_async.sync.aligned.m64n64k16.f32.bf16.bf16 "
      "{%0,%1,%2,%3,%4,%5,%6,%7,%8,%9,%10,%11,%12,%13,%14,%15,%16,%17,%18,%19,%20,%21,%22,%23,%24,%25,%26,%27,%28,%29,%30,%31}, "
      "%32, %33, 1, 1, 1, 0, 1;"
    : "+f"(d[0]), "+f"(d[1]), "+f"(d[2]), "+f"(d[3]), "+f"(d[4]), "+f"(d[5]), "+f"(d[6]), "+f"(d[7]), "+f"(d[8]),
      "+f"(d[9]), "+f"(d[10]), "+f"(d[11]), "+f"(d[12]), "+f"(d[13]), "+f"(d[14]), "+f"(d[15]), "+f"(d[16]),
      "+f"(d[17]), "+f"(d[18]), "+f"(d[19]), "+f"(d[20]), "+f"(d[21]), "+f"(d[22]), "+f"(d[23]), "+f"(d[24]),
      "+f"(d[25]), "+f"(d[26]), "+f"(d[27]), "+f"(d[28]), "+f"(d[29]), "+f"(d[30]), "+f"(d[31])
    : "l"(da), "l"(db));
}
__device__ __forceinline__ void wgmma_gemm_n192(float (&d)[96], uint64_t da, uint64_t db) {
  asm volatile("wgmma.mma_async.sync.aligned.m64n192k16.f32.bf16.bf16 "
      "{%0,%1,%2,%3,%4,%5,%6,%7,%8,%9,%10,%11,%12,%13,%14,%15,%16,%17,%18,%19,%20,%21,%22,%23,%24,%25,%26,%27,%28,%29,%30,%31,%32,%33,%34,%35,%36,%37,%38,%39,%40,%41,%42,%43,%44,%45,%46,%47,%48,%49,%50,%51,%52,%53,%54,%55,%56,%57,%58,%59,%60,%61,%62,%63,%64,%65,%66,%67,%68,%69,%70,%71,%72,%73,%74,%75,%76,%77,%78,%79,%80,%81,%82,%83,%84,%85,%86,%87,%88,%89,%90,%91,%92,%93,%94,%95}, "
      "%96, %97, 1, 1, 1, 0, 1;"
    : "+f"(d[0]), "+f"(d[1]), "+f"(d[2]), "+f"(d[3]), "+f"(d[4]), "+f"(d[5]), "+f"(d[6]), "+f"(d[7]), "+f"(d[8]),
      "+f"(d[9]), "+f"(d[10]), "+f"(d[11]), "+f"(d[12]), "+f"(d[13]), "+f"(d[14]), "+f"(d[15]), "+f"(d[16]),
      "+f"(d[17]), "+f"(d[18]), "+f"(d[19]), "+f"(d[20]), "+f"(d[21]), "+f"(d[22]), "+f"(d[23]), "+f"(d[24]),
      "+f"(d[25]), "+f"(d[26]), "+f"(d[27]), "+f"(d[28]), "+f"(d[29]), "+f"(d[30]), "+f"(d[31]), "+f"(d[32]),
      "+f"(d[33]), "+f"(d[34]), "+f"(d[35]), "+f"(d[36]), "+f"(d[37]), "+f"(d[38]), "+f"(d[39]), "+f"(d[40]),
      "+f"(d[41]), "+f"(d[42]), "+f"(d[43]), "+f"(d[44]), "+f"(d[45]), "+f"(d[46]), "+f"(d[47]), "+f"(d[48]),
      "+f"(d[49]), "+f"(d[50]), "+f"(d[51]), "+f"(d[52]), "+f"(d[53]), "+f"(d[54]), "+f"(d[55]), "+f"(d[56]),
      "+f"(d[57]), "+f"(d[58]), "+f"(d[59]), "+f"(d[60]), "+f"(d[61]), "+f"(d[62]), "+f"(d[63]), "+f"(d[64]),
      "+f"(d[65]), "+f"(d[66]), "+f"(d[67]), "+f"(d[68]), "+f"(d[69]), "+f"(d[70]), "+f"(d[71]), "+f"(d[72]),
      "+f"(d[73]), "+f"(d[74]), "+f"(d[75]), "+f"(d[76]), "+f"(d[77]), "+f"(d[78]), "+f"(d[79]), "+f"(d[80]),
      "+f"(d[81]), "+f"(d[82]), "+f"(d[83]), "+f"(d[84]), "+f"(d[85]), "+f"(d[86]), "+f"(d[87]), "+f"(d[88]),
      "+f"(d[89]), "+f"(d[90]), "+f"(d[91]), "+f"(d[92]), "+f"(d[93]), "+f"(d[94]), "+f"(d[95])
    : "l"(da), "l"(db));
}

constexpr float QSCALE = 0.25f * 1.4426950408889634f;
constexpr float LN_EPS = 1e-5f;

__device__ __forceinline__ void row_stats(int layer, int row, float& mu, float& rstd) {
  const float4* p = reinterpret_cast<const float4*>(g_stats + (layer * S_ + row) * 8);
  float4 a = __ldcg(p), b = __ldcg(p + 1), c = __ldcg(p + 2), d = __ldcg(p + 3);
  float s = (a.x + a.z) + (b.x + b.z) + (c.x + c.z) + (d.x + d.z);
  float q = (a.y + a.w) + (b.y + b.w) + (c.y + c.w) + (d.y + d.w);
  mu = s * (1.f / D_);
  float var = fmaxf(q * (1.f / D_) - mu * mu, 0.f);
  rstd = rsqrtf(var + LN_EPS);
}

__global__ void __launch_bounds__(256) prep_kernel(const __nv_bfloat16* __restrict__ x, const __nv_bfloat16* __restrict__ wqkv,
                                                   const __nv_bfloat16* __restrict__ wq, const __nv_bfloat16* __restrict__ wk,
                                                   const __nv_bfloat16* __restrict__ wv) {
  TM(0, 0);
  pdl_launch();
  __shared__ float red[8][16];
  const int b = blockIdx.x, tid = threadIdx.x, lane = tid & 31, warp = tid >> 5;
  {
    const __nv_bfloat16* w; int ld, out;
    if (b < 96) { w = wqkv + b * 16; ld = 1536; out = b * 16; }
    else if (b < 128) { w = wq + (b - 96) * 16; ld = 512; out = 1536 + (b - 96) * 16; }
    else { w = (b == 128) ? wk : wv; ld = 16; out = 2048 + (b - 128) * 16; }
    const int half = tid & 1, r0 = tid >> 1;
    float acc[8];
#pragma unroll
    for (int i = 0; i < 8; i++) acc[i] = 0.f;
#pragma unroll
    for (int j = 0; j < 4; j++) {
      uint4 v = __ldg(reinterpret_cast<const uint4*>(w + (size_t)(r0 + 128 * j) * ld + half * 8));
      if (b >= 128) *reinterpret_cast<uint4*>(g_wkv + (r0 + 128 * j) * 32 + (b - 128) * 16 + half * 8) = v;
      acc[0] += bf_lo(v.x); acc[1] += bf_hi(v.x); acc[2] += bf_lo(v.y); acc[3] += bf_hi(v.y);
      acc[4] += bf_lo(v.z); acc[5] += bf_hi(v.z); acc[6] += bf_lo(v.w); acc[7] += bf_hi(v.w);
    }
#pragma unroll
    for (int i = 0; i < 8; i++) {
#pragma unroll
      for (int o = 2; o < 32; o <<= 1) acc[i] += __shfl_xor_sync(0xffffffffu, acc[i], o);
    }
    if (lane < 2) {
#pragma unroll
      for (int i = 0; i < 8; i++) red[warp][lane * 8 + i] = acc[i];
    }
    __syncthreads();
    if (tid < 16) {
      float s = 0.f;
#pragma unroll
      for (int w8 = 0; w8 < 8; w8++) s += red[w8][tid];
      g_colsum[out + tid] = s;
    }
    if (b == 129 && tid >= 32 && tid < 64) g_colsum[2048 + tid] = 0.f;
  }
  if (b < 128) {
#pragma unroll
    for (int j = 0; j < 2; j++) {
      const int row = b * 16 + warp * 2 + j;
      const uint4* p = reinterpret_cast<const uint4*>(x + (size_t)row * D_ + lane * 16);
      uint4 v0 = __ldg(p), v1 = __ldg(p + 1);
      uint32_t u[8] = {v0.x, v0.y, v0.z, v0.w, v1.x, v1.y, v1.z, v1.w};
      float s = 0.f, q = 0.f;
#pragma unroll
      for (int i = 0; i < 8; i++) {
        float a = bf_lo(u[i]), c = bf_hi(u[i]);
        s += a + c; q = fmaf(a, a, fmaf(c, c, q));
      }
      s += __shfl_xor_sync(0xffffffffu, s, 1); q += __shfl_xor_sync(0xffffffffu, q, 1);
      s += __shfl_xor_sync(0xffffffffu, s, 2); q += __shfl_xor_sync(0xffffffffu, q, 2);
      if ((lane & 3) == 0) g_stats[row * 8 + (lane >> 2)] = make_float2(s, q);
    }
  }
  TM(0, 4);
}

__device__ __forceinline__ int tok0(int r, int rb) { return (rb >> 2) * 512 + r * 256 + (rb & 3) * 64; }
__device__ __forceinline__ int key_pos(int token) {
  const int r = (token >> 8) & 1, rb = ((token >> 9) << 2) | ((token >> 6) & 3), row = token & 63;
  return (16 * r + (row >> 2)) * 64 + rb * 4 + (row & 3);
}
__device__ __forceinline__ float sq_norm16(const uint4& a, const uint4& b) {
  const uint32_t u[8] = {a.x, a.y, a.z, a.w, b.x, b.y, b.z, b.w};
  __half2 n = __hmul2(*reinterpret_cast<const __half2*>(&u[0]), *reinterpret_cast<const __half2*>(&u[0]));
#pragma unroll
  for (int i = 1; i < 8; i++) n = __hfma2(*reinterpret_cast<const __half2*>(&u[i]), *reinterpret_cast<const __half2*>(&u[i]), n);
  return __low2float(n) + __high2float(n);
}
__device__ __forceinline__ uint32_t hsub2(uint32_t a, uint32_t b) {
  uint32_t d; asm("sub.rn.f16x2 %0, %1, %2;" : "=r"(d) : "r"(a), "r"(b)); return d;
}
__device__ __forceinline__ void proj_store(uint32_t a, uint32_t ap, int type, int layer, int head, int token) {
  const uint4 v0 = lds128(a), v1 = lds128(a + 16);
  const size_t hb = (size_t)((layer & 1) * H_ + head) * (S_ * 2);
  if (type == 2) {
    uint4* dst = g_v + hb + key_pos(token);
    dst[0] = v0; dst[S_] = v1;
    return;
  }
  if (type == 0) {
    uint4* dst = g_q + hb + (token >> 3) * 16 + (token & 7);
    dst[0] = v0; dst[8] = v1;
  } else {
    uint4 d0 = v0, d1 = v1;
    if (ap) {
      const uint4 p0 = lds128(ap), p1 = lds128(ap + 16);
      d0 = make_uint4(hsub2(v0.x, p0.x), hsub2(v0.y, p0.y), hsub2(v0.z, p0.z), hsub2(v0.w, p0.w));
      d1 = make_uint4(hsub2(v1.x, p1.x), hsub2(v1.y, p1.y), hsub2(v1.z, p1.z), hsub2(v1.w, p1.w));
    }
    const int pos = key_pos(token);
    uint4* dst = g_k + hb + (pos >> 3) * 16 + (pos & 7);
    dst[0] = d0; dst[8] = d1;
  }
  const unsigned m = __reduce_max_sync(0xffffffffu, __float_as_uint(sq_norm16(v0, v1)) & 0x7fffffffu);
  if ((threadIdx.x & 31) == 0) g_nrm[((layer * 2 + type) * H_ + head) * 64 + (token >> 5)] = __uint_as_float(m);
}
template <bool F16, int N>
__device__ __forceinline__ void proj_stage(const float (&acc)[N], int j  , uint32_t addr, const float* cs,
                                           float mu0, float f0, float mu1, float f1) {
  uint32_t r[4];
#pragma unroll
  for (int e = 0; e < 2; e++) {
    const float2 c = *reinterpret_cast<const float2*>(cs + (j + e) * 8);
    const float a0 = fmaf(-mu0, c.x, acc[(j + e) * 4 + 0]) * f0, a1 = fmaf(-mu0, c.y, acc[(j + e) * 4 + 1]) * f0;
    const float a2 = fmaf(-mu1, c.x, acc[(j + e) * 4 + 2]) * f1, a3 = fmaf(-mu1, c.y, acc[(j + e) * 4 + 3]) * f1;
    r[e * 2] = F16 ? pack_f16(a0, a1) : pack_bf16(a0, a1);
    r[e * 2 + 1] = F16 ? pack_f16(a2, a3) : pack_bf16(a2, a3);
  }
  stsm4(addr + j * 16, r[0], r[1], r[2], r[3]);
}

constexpr int G1A_NS = 5, G1A_STAGE = 16384 + 3 * 8192, G1A_PITCH = 400;
constexpr int G1A_SMEM = G1A_NS * G1A_STAGE + 1024 + 192 * 4 + 128;
__global__ void __launch_bounds__(288, 1) g1a_kernel(const __grid_constant__ CUtensorMap mx, const __grid_constant__ CUtensorMap mw) {
  extern __shared__ uint8_t smem_raw[];
  const uint32_t sbase = (s2u(smem_raw) + 1023) & ~1023u;
  const uint32_t s_cs = sbase + G1A_NS * G1A_STAGE, s_bar = s_cs + 192 * 4;
  float* cs = reinterpret_cast<float*>(smem_raw + (s_cs - s2u(smem_raw)));
  const int tid = threadIdx.x, warp = tid >> 5, lane = tid & 31;
  const int nb = blockIdx.x & 7, rb = blockIdx.x >> 3;
  TM(1, 0);
  if (tid == 0) {
    for (int i = 0; i < G1A_NS; i++) { mbar_init(s_bar + i * 8, 1); mbar_init(s_bar + 40 + i * 8, 2); }
    fence_bar_init();
  }
  __syncthreads();
  if (warp == 8) {
    if (lane == 0) {
      for (int c = 0; c < 8; c++) {
        const int s = c < G1A_NS ? c : c - G1A_NS;
        const uint32_t st = sbase + s * G1A_STAGE, bar = s_bar + s * 8;
        if (c >= G1A_NS) mbar_wait(s_bar + 40 + s * 8, 0);
        mbar_expect(bar, G1A_STAGE);
        tma_load(st, &mx, c * 64, tok0(0, rb), bar);
        tma_load(st + 8192, &mx, c * 64, tok0(1, rb), bar);
        for (int j = 0; j < 3; j++) tma_load(st + 16384 + j * 8192, &mw, nb * 192 + j * 64, c * 64, bar);
      }
    }
    return;
  }
  const int wg = warp >> 2;
  float acc[96];
#pragma unroll
  for (int i = 0; i < 96; i++) acc[i] = 0.f;
  pin(acc);
#pragma unroll 1
  for (int c = 0; c < 8; c++) {
    const int s = c < G1A_NS ? c : c - G1A_NS;
    mbar_wait(s_bar + s * 8, c >= G1A_NS);
    if (c == 0) TM(1, 2);
    const uint32_t st = sbase + s * G1A_STAGE;
    const uint64_t da = mkdesc(st + wg * 8192, 16, 1024, 1), db = mkdesc(st + 16384, 8192, 1024, 1);
    wg_fence();
#pragma unroll
    for (int k = 0; k < 4; k++) wgmma_gemm_n192(acc, da + k * 2, db + k * 128);
    wg_commit();
    if (c >= 1 && c <= 3) { wg_wait<1>(); if ((tid & 127) == 0) mbar_arrive(s_bar + 40 + (c - 1) * 8); }
    if (c == 5) {
      pdl_wait();
      pdl_launch();
      if (tid < 192) cs[tid] = __ldcg(g_colsum + nb * 192 + tid);
    }
  }
  float mu0, rs0, mu1, rs1;
  const int row0 = tok0(wg, rb) + (warp & 3) * 16 + (lane >> 2);
  row_stats(0, row0, mu0, rs0); row_stats(0, row0 + 8, mu1, rs1);
  wg_wait<0>();
  pin(acc);
  TM(1, 3);
  named_sync(1, 256);
  {
    const uint32_t addr = sbase + (wg * 64 + (warp & 3) * 16 + (lane & 15)) * G1A_PITCH + (lane >> 4) * 16;
#pragma unroll
    for (int j = 0; j < 24; j += 2) {
      const int type = (nb * 12 + (j >> 1)) >> 5;
      const float sc = type == 0 ? QSCALE : 1.f;
      if (type == 2) proj_stage<false>(acc, j, addr, cs + (lane & 3) * 2, mu0, rs0, mu1, rs1);
      else proj_stage<true>(acc, j, addr, cs + (lane & 3) * 2, mu0, rs0 * sc, mu1, rs1 * sc);
    }
  }
  named_sync(1, 256);
#pragma unroll
  for (int it = 0; it < 6; it++) {
    const int item = warp + it * 8, hh = item >> 2, trow = (item & 3) * 32 + lane;
    const int hg = nb * 12 + hh;
    const uint32_t a = sbase + trow * G1A_PITCH + hh * 32;
    proj_store(a, trow >= 4 ? a - 4 * G1A_PITCH : 0u, hg >> 5, 0, hg & 31, tok0(trow >> 6, rb) + (trow & 63));
  }
  TM(1, 4);
}

constexpr uint32_t MUFU_MASK = 0xF800u;
constexpr float EXP_MAGIC = 383.0f + 0.65f / 128.0f;
constexpr uint32_t POLY_A = 0x5a835a83u, POLY_B = 0x92a192a1u, POLY_C = 0x800b800bu;
constexpr float SCORE_LIMIT = 116.f;

__device__ __forceinline__ void exp_step(const float (&s)[32], uint32_t (&p)[16], uint32_t pb) {
#pragma unroll
  for (int i = 0; i < 16; i++) {
    if ((MUFU_MASK >> i) & 1) {
      float a, b;
      asm("ex2.approx.ftz.f32 %0, %1;" : "=f"(a) : "f"(s[2 * i]));
      asm("ex2.approx.ftz.f32 %0, %1;" : "=f"(b) : "f"(s[2 * i + 1]));
      p[i] = pack_bf16(a, b);
    } else {
      uint32_t z, u, h;
      asm("prmt.b32 %0, %1, %2, 0x6521;" : "=r"(z) : "r"(__float_as_uint(s[2 * i])), "r"(__float_as_uint(s[2 * i + 1])));
      asm("fma.rn.f16x2 %0, %1, %2, %3;" : "=r"(u) : "r"(z & 0x007f007fu), "r"(POLY_A), "r"(pb));
      asm("fma.rn.f16x2 %0, %1, %1, %2;" : "=r"(h) : "r"(u), "r"(POLY_C));
      p[i] = z - h;
    }
  }
}

__device__ __forceinline__ void pv4(float (&o)[12], const uint32_t (&p)[16], uint64_t dv) {
#pragma unroll
  for (int j = 0; j < 4; j++) wgmma_pv_n24(o, p[4 * j], p[4 * j + 1], p[4 * j + 2], p[4 * j + 3], dv + j * 16);
}
template <bool PV>
__device__ __forceinline__ void att_step(float (&s)[32], float (&o)[12], uint32_t (&pin_)[16], uint32_t (&pout)[16], uint64_t dq,
                                         uint64_t dk, uint64_t dv, uint32_t pb) {
  pin(s);
  if (PV) pin(pin_);
  wg_fence();
  wgmma_qk_n64(s, dq, dk);
  wg_commit();
  if (PV) {
#pragma unroll
    for (int j = 0; j < 4; j++) wgmma_pv_n24(o, pin_[4 * j], pin_[4 * j + 1], pin_[4 * j + 2], pin_[4 * j + 3], dv + j * 16);
    wg_commit();
    wg_wait<1>();
  } else {
    wg_wait<0>();
  }
  pin(s);
  exp_step(s, pout, pb);
  pin(pout);
}

constexpr int M_STAGE = 0;
constexpr int M_STG = 65536, STG_PITCH = 144;
constexpr int M_KV = 74752;
constexpr int M_Q = M_KV + 17 * 8192;
constexpr int M_CS = M_Q + 16384, M_KTAIL = M_CS + 768, M_ROW = M_KTAIL + 512, M_BAR = M_ROW + 512;
constexpr int MEGA_SMEM = M_BAR + 256;
__device__ __forceinline__ int k_unit(int j) { return j < 2 ? 7 + 2 * j : j - 2; }
__device__ __forceinline__ int v0_unit(int b) { return b == 0 ? 14 : 12 - 2 * b; }
__device__ __forceinline__ int v_stride(int b) { return b == 0 ? 1 : b + 2; }
constexpr int B_FULL = 0, B_EMPTY = 32, B_KV = 64, B_Q = 80, B_FREE0 = 96, B_ODONE = 104, B_RES = 120, B_PRE = 128,
              B_TURN = 136, B_EPI = 168;

struct MegaParams {
  CUtensorMap m[8];
  const __nv_bfloat16* x0;
  const __nv_bfloat16* wqkv; const __nv_bfloat16* wq; const __nv_bfloat16* wk;
  __nv_bfloat16* out;
};

__device__ __forceinline__ void cnt_signal(int idx) {
  if (elect_one()) asm volatile("red.release.gpu.global.add.u32 [%0], 1;" ::"l"(g_cnt + idx) : "memory");
}
__device__ __forceinline__ void cnt_wait(int idx, unsigned target) {
  unsigned v;
  int it = 0;
  while (true) {
    asm volatile("ld.acquire.gpu.global.u32 %0, [%1];" : "=r"(v) : "l"(g_cnt + idx) : "memory");
    if (v >= target) break;
    if (++it > (1 << 24)) __trap();
    __nanosleep(40);
  }
  asm volatile("fence.proxy.async.global;" ::: "memory");
}

__device__ __forceinline__ void att_fallback(const MegaParams& P, int layer, int head, int row0, __nv_bfloat16* sk, int bar_id) {
  const int t = threadIdx.x & 127, hf = t & 1;
  const __nv_bfloat16* x = layer == 0 ? P.x0 : g_x + (size_t)(layer - 1) * S_ * D_;
  const bool mqa = layer & 1;
  const __nv_bfloat16* vimg = reinterpret_cast<const __nv_bfloat16*>(g_v + (size_t)((layer & 1) * H_ + (mqa ? 0 : head)) * (S_ * 2));
  float q[16], o[16], acc[16];
  float m = -INFINITY, l = 0.f;
#pragma unroll
  for (int d = 0; d < 16; d++) { o[d] = 0.f; q[d] = 0.f; }
#pragma unroll 1
  for (int ch = -1; ch < 32; ch++) {
    const int token = ch < 0 ? row0 + (t >> 1) : ch * 64 + (t >> 1);
    const __nv_bfloat16* w = ch < 0 ? (mqa ? P.wq : P.wqkv) + head * 16 : (mqa ? P.wk : P.wqkv + 512 + head * 16);
    const int ld = mqa ? (ch < 0 ? 512 : 16) : 1536;
    float mu, rs;
    row_stats(layer, token, mu, rs);
#pragma unroll
    for (int d = 0; d < 16; d++) acc[d] = 0.f;
#pragma unroll 1
    for (int k = hf * 256; k < hf * 256 + 256; k++) {
      const unsigned short xr = __ldcg(reinterpret_cast<const unsigned short*>(x) + (size_t)token * D_ + k);
      const float xn = __bfloat162float(__float2bfloat16((__uint_as_float((uint32_t)xr << 16) - mu) * rs));
#pragma unroll
      for (int d = 0; d < 16; d++) acc[d] = fmaf(xn, __bfloat162float(w[(size_t)k * ld + d]), acc[d]);
    }
#pragma unroll
    for (int d = 0; d < 16; d++) acc[d] = __bfloat162float(__float2bfloat16(acc[d] + __shfl_xor_sync(0xffffffffu, acc[d], 1)));
    if (ch < 0) {
#pragma unroll
      for (int d = 0; d < 16; d++) q[d] = acc[d];
      continue;
    }
    named_sync(bar_id, 128);
    if (hf == 0) {
#pragma unroll
      for (int d = 0; d < 16; d++) sk[(t >> 1) * 16 + d] = __float2bfloat16(acc[d]);
    }
    named_sync(bar_id, 128);
#pragma unroll 1
    for (int j = hf * 32; j < hf * 32 + 32; j++) {
      float sc = 0.f;
#pragma unroll
      for (int d = 0; d < 16; d++) sc = fmaf(q[d], __bfloat162float(sk[j * 16 + d]), sc);
      sc *= 0.25f;
      if (sc > m || sc != sc) {
        const float a = __expf(m - sc);
        l *= a;
#pragma unroll
        for (int d = 0; d < 16; d++) o[d] *= a;
        m = sc;
      }
      const float p = __expf(sc - m);
      l += p;
      const int pos = key_pos(ch * 64 + j);
#pragma unroll
      for (int d = 0; d < 16; d++) {
        const unsigned short vr = __ldcg(reinterpret_cast<const unsigned short*>(vimg) + (d >> 3) * (S_ * 8) + pos * 8 + (d & 7));
        o[d] = fmaf(p, __uint_as_float((uint32_t)vr << 16), o[d]);
      }
    }
  }
  const float m2 = __shfl_xor_sync(0xffffffffu, m, 1), mm = fmaxf(m, m2), a = __expf(m - mm);
  l *= a; l += __shfl_xor_sync(0xffffffffu, l, 1);
  const float inv = 1.f / l;
  __nv_bfloat16* dst = g_o + (size_t)(row0 + (t >> 1)) * D_ + head * 16;
#pragma unroll
  for (int d = 0; d < 16; d++) {
    float v = o[d] * a; v += __shfl_xor_sync(0xffffffffu, v, 1);
    if ((d >> 3) == hf) dst[d] = __float2bfloat16(v * inv);
  }
}

__device__ __forceinline__ const CUtensorMap* b_map(const MegaParams& P, int code) {
  const int l = code >> 3, p = code & 3;
  return &P.m[p == 0 ? 5 + (l & 1) : ((l & 1) ? 2 : (p == 3 ? 3 : 4))];
}
__device__ __forceinline__ int b_col(int code) {
  const int p = code & 3, ct = blockIdx.x & 7;
  return p == 0 || p == 3 ? ct * 64 : ((code & 8) ? p * 512 + ct * 64 : 0);
}
__device__ __forceinline__ void issue_b(uint32_t sbase, const CUtensorMap* m, int col, int st, int c) {
  mbar_expect(sbase + M_BAR + B_FULL + st * 8, 16384);
  tma_load(sbase + M_STAGE + st * 16384 + 8192, m, col, c * 64, sbase + M_BAR + B_FULL + st * 8);
}
__device__ __forceinline__ void issue_a(uint32_t sbase, const CUtensorMap* m, int row, int st, int c) {
  tma_load(sbase + M_STAGE + st * 16384, m, c * 64, row, sbase + M_BAR + B_FULL + st * 8);
}
__device__ __forceinline__ void load_kv(uint32_t sbase, int l, int r) {
  const size_t hb = (size_t)((l & 1) * H_ + ((l & 1) ? 0 : blockIdx.x >> 2)) * 65536;
  const uint8_t* gk = reinterpret_cast<const uint8_t*>(g_k) + hb;
  const uint8_t* gv = reinterpret_cast<const uint8_t*>(g_v) + hb;
  const uint32_t bar = sbase + M_BAR + B_KV + r * 8;
  if (elect_one()) {
    mbar_expect(bar, 65536);
#pragma unroll
    for (int j = 0; j < 2; j++) {
      const int b = r * 2 + j;
      bulk_load(sbase + M_KV + k_unit(2 * b) * 8192, gk + b * 16384, 8192, bar);
      bulk_load(sbase + M_KV + v0_unit(b) * 8192, gv + b * 8192, 8192, bar);
      bulk_load(sbase + M_KV + (v0_unit(b) + v_stride(b)) * 8192, gv + 32768 + b * 8192, 8192, bar);
      bulk_load(sbase + M_KV + k_unit(2 * b + 1) * 8192, gk + b * 16384 + 8192, 8192, bar);
    }
  }
}
__device__ __forceinline__ void load_q(uint32_t sbase, int l, int r) {
  const uint32_t bar = sbase + M_BAR + B_Q + r * 8;
  if (elect_one()) {
    mbar_expect(bar, 8192);
    bulk_load(sbase + M_Q + r * 8192,
              reinterpret_cast<const uint8_t*>(g_q) + (size_t)((l & 1) * H_ + (blockIdx.x >> 2)) * 65536 + (blockIdx.x & 3) * 16384 + r * 8192,
              8192, bar);
  }
}

__device__ __forceinline__ bool pass_exists(int job, int p) {
  return p == 0 || (job < 6 && (p == 3 || (job & 2) || (p == 1 && (blockIdx.x & 7) == 0)));
}
__device__ __forceinline__ int next_pass(int code) {
  const int job = code >> 2, p = code & 3;
  if (p == 0 && pass_exists(job, 1)) return code + 1;
  if (p == 1 && pass_exists(job, 2)) return code + 1;
  if (p < 3 && pass_exists(job, 3)) return job * 4 + 3;
  return job * 4 + 4;
}
__device__ __forceinline__ int prev_pass(int code) {
  const int job = code >> 2, p = code & 3;
  if (p == 0) return job > 6 ? (job - 1) * 4 : (job - 1) * 4 + 3;
  if (p == 3 && pass_exists(job, 2)) return code - 1;
  if (p >= 2 && pass_exists(job, 1)) return job * 4 + 1;
  return job * 4;
}

__device__ __forceinline__ void proj_pass(const MegaParams& P, uint8_t* sm, uint32_t sbase, int code, int wg) {
  const uint32_t s_bar = sbase + M_BAR;
  const int prev = prev_pass(code);
  if (code > 0) mbar_wait_long(s_bar + B_TURN + (prev & 3) * 8, (prev >> 2) & 1);
  float acc[32];
#pragma unroll
  for (int i = 0; i < 32; i++) acc[i] = 0.f;
  pin(acc);
#pragma unroll 1
  for (int h = 0; h < 2; h++) {
    h = __shfl_sync(0xffffffffu, h, 0);
#pragma unroll
    for (int j = 0; j < 4; j++) {
      const uint32_t st = sbase + M_STAGE + j * 16384;
      mbar_wait_long(s_bar + B_FULL + j * 8, h);
      const uint64_t da = mkdesc(st, 16, 1024, 1), db = mkdesc(st + 8192, 8192, 1024, 1);
      wg_fence();
#pragma unroll
      for (int k = 0; k < 4; k++) wgmma_gemm_n64(acc, da + k * 2, db + k * 128);
      wg_commit();
      wg_wait<1>();
      if ((j > 0 || h == 1) && elect_one()) mbar_arrive(s_bar + B_EMPTY + ((j + 3) & 3) * 8);
    }
  }
  wg_wait<0>();
  pin(acc);
  if (elect_one()) { mbar_arrive(s_bar + B_EMPTY + 24); mbar_arrive(s_bar + B_TURN + (code & 3) * 8); }
  int t;
  asm volatile("mov.u32 %0, %%tid.x;" : "=r"(t));
  t &= 127;
  const int lane = t & 31, w4 = t >> 5;
  const int l = code >> 3, r = (code >> 2) & 1, p = code & 3;
  const int rb = blockIdx.x >> 3, ct = blockIdx.x & 7, row0 = tok0(r, rb);
  const uint32_t stg = sbase + M_STG;
  if (p == 0) {
    mbar_wait(s_bar + B_RES, r);
    const uint32_t ra = stg + (w4 * 16 + (lane & 15)) * 128;
    float s0 = 0.f, q0 = 0.f, s1 = 0.f, q1 = 0.f;
#pragma unroll
    for (int j = 0; j < 8; j += 2) {
      const uint32_t a = ra + (((j + (lane >> 4)) ^ (lane & 7)) << 4);
      uint32_t y[4];
      ldsm4(a, y[0], y[1], y[2], y[3]);
#pragma unroll
      for (int e = 0; e < 4; e++) {
        y[e] = hadd2_bf16(y[e], pack_bf16(acc[4 * j + 2 * e], acc[4 * j + 2 * e + 1]));
        const float lo = bf_lo(y[e]), hi = bf_hi(y[e]);
        if (e & 1) { s1 += lo + hi; q1 = fmaf(lo, lo, fmaf(hi, hi, q1)); }
        else { s0 += lo + hi; q0 = fmaf(lo, lo, fmaf(hi, hi, q0)); }
      }
      stsm4(a, y[0], y[1], y[2], y[3]);
    }
    __syncwarp();
    __nv_bfloat16* xout = (l == 3 ? P.out : g_x + (size_t)l * S_ * D_) + (size_t)(row0 + w4 * 16 + (lane >> 3)) * D_ + ct * 64 + (lane & 7) * 8;
#pragma unroll
    for (int i = 0; i < 4; i++) {
      const int rr = i * 4 + (lane >> 3);
      *reinterpret_cast<uint4*>(xout + (size_t)i * 4 * D_) = lds128(stg + (w4 * 16 + rr) * 128 + (((lane & 7) ^ (rr & 7)) << 4));
    }
    if (l < 3) {
#pragma unroll
      for (int o = 1; o < 4; o <<= 1) {
        s0 += __shfl_xor_sync(0xffffffffu, s0, o); q0 += __shfl_xor_sync(0xffffffffu, q0, o);
        s1 += __shfl_xor_sync(0xffffffffu, s1, o); q1 += __shfl_xor_sync(0xffffffffu, q1, o);
      }
      if ((lane & 3) == 0) {
        float2* st = g_stats + ((l + 1) * S_ + row0 + w4 * 16 + (lane >> 2)) * 8 + ct;
        st[0] = make_float2(s0, q0); st[64] = make_float2(s1, q1);
      }
    }
  } else {
    const bool kv = !(l & 1) && p == 1;
    const int type = p == 3 ? 0 : p;
    mbar_wait(s_bar + B_PRE, r);
    mbar_wait(s_bar + B_EPI + (prev & 3) * 8, (prev >> 2) & 1);
    const float2 st0 = reinterpret_cast<const float2*>(sm + M_ROW)[w4 * 16 + (lane >> 2)];
    const float2 st1 = reinterpret_cast<const float2*>(sm + M_ROW)[w4 * 16 + (lane >> 2) + 8];
    const float* cs = reinterpret_cast<const float*>(sm + M_CS) + (p - 1) * 64 + (lane & 3) * 2;
    const uint32_t saddr = stg + (w4 * 16 + (lane & 15)) * STG_PITCH + (lane >> 4) * 16;
    if (kv) {
      proj_stage<true>(acc, 0, saddr, cs, st0.x, st0.y, st1.x, st1.y);
      proj_stage<false>(acc, 2, saddr, cs, st0.x, st0.y, st1.x, st1.y);
    } else if (type == 2) {
#pragma unroll
      for (int j = 0; j < 8; j += 2) proj_stage<false>(acc, j, saddr, cs, st0.x, st0.y, st1.x, st1.y);
    } else {
      const float sc = type == 0 ? QSCALE : 1.f, f0 = st0.y * sc, f1 = st1.y * sc;
#pragma unroll
      for (int j = 0; j < 8; j += 2) proj_stage<true>(acc, j, saddr, cs, st0.x, f0, st1.x, f1);
    }
    named_sync(wg + 1, 128);
    const int row = t & 63;
#pragma unroll
    for (int i = 0; i < 2; i++) {
      if (kv && i == 1) break;
      const int hh = 2 * i + (t >> 6);
      const uint32_t a = stg + row * STG_PITCH + hh * 32;
      const uint32_t ap = row >= 4 ? a - 4 * STG_PITCH : (r ? sbase + M_KTAIL + row * 128 + hh * 32 : 0u);
      proj_store(a, ap, kv ? 1 + hh : type, l + 1, kv ? 0 : ct * 4 + hh, row0 + row);
    }
    if (p == 1 && r == 0 && t < 32)
      *reinterpret_cast<uint4*>(sm + M_KTAIL + t * 16) = lds128(stg + (60 + (t >> 3)) * STG_PITCH + (t & 7) * 16);
  }
  __syncwarp();
  if (lane == 0) mbar_arrive(s_bar + B_EPI + p * 8);
}

__global__ void __launch_bounds__(640, 1) mega_kernel(const __grid_constant__ MegaParams P) {
  extern __shared__ __align__(1024) uint8_t sm[];
  const uint32_t sbase = s2u(sm);
  if (sbase & 1023) __trap();
  const uint32_t s_bar = sbase + M_BAR;
  const int tid = threadIdx.x, warp = tid >> 5, lane = tid & 31;
  TM(2, 0);
  if (tid == 0) {
    for (int i = 0; i < 4; i++) {
      mbar_init(s_bar + B_FULL + i * 8, 1); mbar_init(s_bar + B_EMPTY + i * 8, 4);
      mbar_init(s_bar + B_TURN + i * 8, 4); mbar_init(s_bar + B_EPI + i * 8, 4);
    }
    for (int i = 0; i < 2; i++) { mbar_init(s_bar + B_KV + i * 8, 1); mbar_init(s_bar + B_Q + i * 8, 1); mbar_init(s_bar + B_ODONE + i * 8, 16); }
    mbar_init(s_bar + B_FREE0, 16);
    mbar_init(s_bar + B_RES, 1);
    mbar_init(s_bar + B_PRE, 1);
    fence_bar_init();
  }
  if (tid < 512) *reinterpret_cast<uint4*>(sm + M_KV + 16 * 8192 + tid * 16) = make_uint4(0x3f803f80u, 0x3f803f80u, 0x3f803f80u, 0x3f803f80u);
  fence_async_smem();
  __syncthreads();
  const int wg = __shfl_sync(0xffffffffu, warp >> 2, 0);

  if (wg < 4) {
    asm volatile("setmaxnreg.inc.sync.aligned.u32 112;");
    pdl_wait();
    const int head = blockIdx.x >> 2, quarter = blockIdx.x & 3;
    uint32_t pb = POLY_B;
    asm volatile("" : "+r"(pb));
    float s[32], o[12];
    uint32_t p1[16];
#pragma unroll
    for (int i = 0; i < 32; i++) s[i] = ((MUFU_MASK >> (i >> 1)) & 1) ? 0.f : EXP_MAGIC;
#pragma unroll
    for (int i = 0; i < 12; i++) o[i] = 0.f;
#pragma unroll
    for (int i = 0; i < 16; i++) p1[i] = 0u;
    const uint64_t dkv = mkdesc(sbase + M_KV, 128, 0, 0);
    uint64_t dq = mkdesc(sbase + M_Q + wg * 2048, 128, 256, 0), dvp = 0;
    bool pend = false;
#pragma unroll 1
    for (int it = 0; it < 32; it++) {
      const int lr = it >> 2, b = it & 3, rnd = lr & 1, layer = lr >> 1;
      const uint32_t par = layer & 1;
      if (b == 0) mbar_wait_long(s_bar + B_Q + rnd * 8, par);
      if (b == 2) TM1(3 + lr, 1);
      if (!(b & 1)) mbar_wait_long(s_bar + B_KV + (b >> 1) * 8, par);
      if (b == 0) TM1(3 + lr, 0);
      if (b == 2) TM1(3 + lr, 2);
      const uint64_t dk0 = dkv + (16ull << 32) + (uint32_t)(k_unit(2 * b) * 512), dk1 = dk0 + (b == 0 ? 1024u : 512u);
      const uint64_t dv = dkv + ((uint64_t)(uint32_t)(v_stride(b) * 512) << 32) + (uint32_t)(v0_unit(b) * 512);
      {
        uint32_t p0[16];
        pin(o);
        if (pend) {
          att_step<true>(s, o, p1, p0, dq, dk0, dvp + 448, pb);
          wg_wait<0>();
        } else {
          att_step<false>(s, o, p1, p0, dq, dk0, dvp, pb);
        }
        pin(o);
        att_step<true>(s, o, p0, p1, dq, dk0 + 128, dv, pb);
        att_step<true>(s, o, p1, p0, dq, dk0 + 256, dv + 64, pb);
        att_step<true>(s, o, p0, p1, dq, dk0 + 384, dv + 128, pb);
        att_step<true>(s, o, p1, p0, dq, dk1, dv + 192, pb);
        att_step<true>(s, o, p0, p1, dq, dk1 + 128, dv + 256, pb);
        att_step<true>(s, o, p1, p0, dq, dk1 + 256, dv + 320, pb);
        att_step<true>(s, o, p0, p1, dq, dk1 + 384, dv + 384, pb);
      }
      dvp = dv;
      const int job = ((it + 1) >> 2) - 1, pp = (wg - job) & 3;
      const bool pass = job >= 0 && ((it + 1) & 3) == ((pp + 1) >> 1) && pass_exists(job, pp);
      pend = !(pass || b == 3);
      if (b == 2 && rnd == 1 && elect_one()) mbar_arrive(s_bar + B_FREE0);
      if (pend) { wg_wait<0>(); continue; }
      pin(p1); pin(o);
      wg_fence();
      pv4(o, p1, dv + 448);
      wg_commit();
      wg_wait<0>();
      pin(o); pin(s);
      if (b == 3) {
        int t;
        asm volatile("mov.u32 %0, %%tid.x;" : "=r"(t));
        const int ln = t & 31;
        const int row0 = quarter * 512 + rnd * 256 + wg * 64;
        const float* nq = g_nrm + (layer * 2 * H_ + head) * 64 + (row0 >> 5);
        const float* nk = g_nrm + ((layer * 2 + 1) * H_ + (par ? 0 : head)) * 64;
        const unsigned qn = max(__float_as_uint(__ldcg(nq)), __float_as_uint(__ldcg(nq + 1)));
        const unsigned kn = __reduce_max_sync(0xffffffffu, max(__float_as_uint(__ldcg(nk + ln)), __float_as_uint(__ldcg(nk + 32 + ln))));
        const float l0 = o[8], l1 = o[10];
        float mx = 0.f;
#pragma unroll
        for (int i = 0; i < 8; i++) mx += fabsf(o[i]);
        const float i0 = __fdividef(1.f, l0), i1 = __fdividef(1.f, l1);
        __nv_bfloat16* dst = g_o + (size_t)(row0 + ((t >> 5) & 3) * 16 + (ln >> 2)) * D_ + head * 16 + (ln & 3) * 2;
        *reinterpret_cast<uint32_t*>(dst) = pack_bf16(o[0] * i0, o[1] * i0);
        *reinterpret_cast<uint32_t*>(dst + 8) = pack_bf16(o[4] * i0, o[5] * i0);
        *reinterpret_cast<uint32_t*>(dst + 8 * D_) = pack_bf16(o[2] * i1, o[3] * i1);
        *reinterpret_cast<uint32_t*>(dst + 8 * D_ + 8) = pack_bf16(o[6] * i1, o[7] * i1);
        const bool ok = __uint_as_float(qn) * __uint_as_float(kn) <= SCORE_LIMIT * SCORE_LIMIT && l0 >= 1e-18f && l0 <= 1e37f &&
                        l1 >= 1e-18f && l1 <= 1e37f && mx <= 3e38f;
        uint32_t bad;
        asm volatile("{.reg .pred p, q; setp.eq.u32 p, %1, 0; barrier.red.or.pred.aligned q, %2, 128, p; selp.u32 %0, 1, 0, q;}"
                     : "=r"(bad) : "r"((uint32_t)ok), "r"(wg + 1) : "memory");
        if (bad) {
          att_fallback(P, layer, head, row0, reinterpret_cast<__nv_bfloat16*>(sm + M_Q + rnd * 8192 + wg * 2048), wg + 1);
          fence_async_smem();
        }
        __syncwarp();
        if (elect_one()) mbar_arrive(s_bar + B_ODONE + rnd * 8);
        TM1(3 + lr, 3);
#pragma unroll
        for (int i = 0; i < 32; i++) s[i] = ((MUFU_MASK >> (i >> 1)) & 1) ? 0.f : EXP_MAGIC;
#pragma unroll
        for (int i = 0; i < 12; i++) o[i] = 0.f;
        dq += rnd ? -512ll : 512ll;
      }
      if (pass) {
        TM3(24 + job * 4 + pp, 0);
        proj_pass(P, sm, sbase, job * 4 + pp, wg);
        TM3(24 + job * 4 + pp, 1);
      }
#pragma unroll
      for (int i = 0; i < 16; i++) asm volatile("mov.b32 %0, 0;" : "=r"(p1[i]));
    }
  } else {
    asm volatile("setmaxnreg.dec.sync.aligned.u32 32;");
    const int w4 = __shfl_sync(0xffffffffu, warp & 3, 0);
    const int rb = blockIdx.x >> 3, ct = blockIdx.x & 7;
    if (w4 == 0) {
      int code = 0;
      bool gated = true;
#pragma unroll 1
      while (code < 32) {
        code = __shfl_sync(0xffffffffu, code, 0);
        const int job = code >> 2, p = code & 3;
        const CUtensorMap* mb = b_map(P, code);
        const CUtensorMap* ma = &P.m[p == 0 ? 1 : 0];
        const int colb = b_col(code), rowa = tok0(job & 1, rb) + (p == 0 ? 0 : (code >> 3) * S_);
#pragma unroll 1
        for (int c = 0; c < 4; c++) {
          if (code > 0) mbar_wait_long(s_bar + B_EMPTY + c * 8, 1);
          if (elect_one()) {
            issue_b(sbase, mb, colb, c, c);
            if (!gated) issue_a(sbase, ma, rowa, c, c);
          }
        }
        if (gated) {
          if (p == 0) {
            if (code == 0) pdl_wait();
            else { const int prev = prev_pass(code); mbar_wait_long(s_bar + B_EPI + (prev & 3) * 8, (prev >> 2) & 1); }
            if (elect_one()) {
              asm volatile("fence.proxy.async;" ::: "memory");
              mbar_expect(s_bar + B_RES, 8192);
              tma_load(sbase + M_STG, &P.m[job < 2 ? 7 : 0], ct * 64, tok0(job & 1, rb) + (job < 2 ? 0 : ((job >> 1) - 1) * S_), s_bar + B_RES);
            }
            mbar_wait_long(s_bar + B_ODONE + (job & 1) * 8, (job >> 1) & 1);
            cnt_wait(CNT_O + job * 4 + (rb >> 2), 32);
            TM2(12 + job, 1);
          } else {
            mbar_wait_long(s_bar + B_EPI, job & 1);
            cnt_wait(CNT_X + job * 16 + rb, 8);
            TM2(12 + job, 3);
          }
          if (elect_one()) {
#pragma unroll
            for (int c = 0; c < 4; c++) issue_a(sbase, ma, rowa, c, c);
          }
        }
#pragma unroll 1
        for (int c = 0; c < 4; c++) {
          mbar_wait_long(s_bar + B_EMPTY + c * 8, 0);
          if (elect_one()) {
            issue_b(sbase, mb, colb, c, c + 4);
            issue_a(sbase, ma, rowa, c, c + 4);
          }
        }
        code = next_pass(code);
        gated = p == 0 || (code & 3) == 0;
      }
    } else if (w4 == 1) {
#pragma unroll 1
      for (int job = 0; job < 8; job++) {
        mbar_wait_long(s_bar + B_ODONE + (job & 1) * 8, (job >> 1) & 1);
        cnt_signal(CNT_O + job * 4 + (blockIdx.x & 3));
        if (job >= 6) continue;
        mbar_wait_long(s_bar + B_EPI, job & 1);
        cnt_signal(CNT_X + job * 16 + rb);
        if (pass_exists(job, 1)) {
          mbar_wait_long(s_bar + B_EPI + 8, job & 1);
          if (job & 2) mbar_wait_long(s_bar + B_EPI + 16, job & 1);
          cnt_signal(CNT_KV + job * 8 + ct);
        }
        mbar_wait_long(s_bar + B_EPI + 24, job & 1);
        cnt_signal(CNT_Q + (job * 4 + (rb >> 2)) * 8 + ct);
      }
    } else if (w4 == 2) {
      pdl_wait();
      load_q(sbase, 0, 0); load_kv(sbase, 0, 0); load_kv(sbase, 0, 1); load_q(sbase, 0, 1);
#pragma unroll 1
      for (int job = 0; job < 6; job++) {
        const int l = job >> 1, r = job & 1;
        mbar_wait_long(s_bar + B_ODONE + r * 8, l & 1);
        if (r == 0) mbar_wait_long(s_bar + B_FREE0, l & 1);
        mbar_wait_long(s_bar + B_TURN, job & 1);
        cnt_wait(CNT_KV + job * 8 + ((l & 1) ? blockIdx.x >> 4 : 0), 16);
        load_kv(sbase, l + 1, r);
        cnt_wait(CNT_Q + (job * 4 + (blockIdx.x & 3)) * 8 + (blockIdx.x >> 4), 4);
        load_q(sbase, l + 1, r);
      }
    } else {
      pdl_wait();
#pragma unroll 1
      for (int job = 0; job < 6; job++) {
        float c[6];
#pragma unroll
        for (int i = 0; i < 6; i++) {
          const int p = 1 + (i >> 1);
          c[i] = __ldcg(g_colsum + ((job & 2) ? (p == 3 ? 0 : p * 512) + ct * 64 : (p == 3 ? 1536 + ct * 64 : 2048)) + (i & 1) * 32 + lane);
        }
        mbar_wait_long(s_bar + B_EPI, job & 1);
        cnt_wait(CNT_X + job * 16 + rb, 8);
#pragma unroll
        for (int i = 0; i < 6; i++) reinterpret_cast<float*>(sm + M_CS)[i * 32 + lane] = c[i];
#pragma unroll 1
        for (int i = 0; i < 2; i++) {
          float mu, rs;
          row_stats((job >> 1) + 1, tok0(job & 1, rb) + i * 32 + lane, mu, rs);
          reinterpret_cast<float2*>(sm + M_ROW)[i * 32 + lane] = make_float2(mu, rs);
        }
        __syncwarp();
        if (elect_one()) mbar_arrive(s_bar + B_PRE);
      }
    }
    named_sync(5, 128);
    if (tid == 512) {
      unsigned old;
      asm volatile("atom.acq_rel.gpu.global.add.u32 %0, [%1], 1;" : "=r"(old) : "l"(g_cnt + CNT_DONE) : "memory");
      if (old == gridDim.x - 1)
        for (int i = 0; i < CNT_N; i++) g_cnt[i] = 0u;
    }
  }
}

typedef CUresult (*EncodeFn)(CUtensorMap*, CUtensorMapDataType, cuuint32_t, void*, const cuuint64_t*, const cuuint64_t*,
                             const cuuint32_t*, const cuuint32_t*, CUtensorMapInterleave, CUtensorMapSwizzle,
                             CUtensorMapL2promotion, CUtensorMapFloatOOBfill);

void make_map(EncodeFn enc, CUtensorMap* m, const void* p, int rows, int cols) {
  cuuint64_t dim[2] = {(cuuint64_t)cols, (cuuint64_t)rows};
  cuuint64_t str[1] = {(cuuint64_t)cols * 2};
  cuuint32_t box[2] = {64, 64};
  cuuint32_t es[2] = {1, 1};
  enc(m, CU_TENSOR_MAP_DATA_TYPE_BFLOAT16, 2, const_cast<void*>(p), dim, str, box, es, CU_TENSOR_MAP_INTERLEAVE_NONE,
      CU_TENSOR_MAP_SWIZZLE_128B, CU_TENSOR_MAP_L2_PROMOTION_L2_128B, CU_TENSOR_MAP_FLOAT_OOB_FILL_NONE);
}

template <typename... KA, typename... A>
void launch(void (*k)(KA...), int grid, int block, int smem, bool pdl, A... args) {
  cudaLaunchConfig_t cfg = {};
  cfg.gridDim = dim3(grid); cfg.blockDim = dim3(block); cfg.dynamicSmemBytes = smem; cfg.stream = cudaStreamPerThread;
  cudaLaunchAttribute at[1];
  at[0].id = cudaLaunchAttributeProgrammaticStreamSerialization;
  at[0].val.programmaticStreamSerializationAllowed = 1;
  cfg.attrs = at; cfg.numAttrs = pdl ? 1 : 0;
  cudaLaunchKernelEx(&cfg, k, KA(args)...);
}

struct HostState {
  bool init;
  const void* in[8];
  MegaParams mp;
};
HostState hs;

}

extern "C" void kernel_launch(void* const* d_in, const int* in_sizes, int n_in, void* d_out, int out_size) {
  const __nv_bfloat16* A_x = (const __nv_bfloat16*)d_in[0];
  const __nv_bfloat16* A_wqkv = (const __nv_bfloat16*)d_in[1];
  const __nv_bfloat16* A_wo = (const __nv_bfloat16*)d_in[2];
  const __nv_bfloat16* B_wq = (const __nv_bfloat16*)d_in[4];
  const __nv_bfloat16* B_wk = (const __nv_bfloat16*)d_in[5];
  const __nv_bfloat16* B_wv = (const __nv_bfloat16*)d_in[6];
  const __nv_bfloat16* B_wo = (const __nv_bfloat16*)d_in[7];
  bool same = hs.init;
  for (int i = 0; i < 8; i++) same = same && hs.in[i] == d_in[i];
  if (!same) {
    void* fn = nullptr;
    cudaDriverEntryPointQueryResult qr;
    cudaGetDriverEntryPoint("cuTensorMapEncodeTiled", &fn, cudaEnableDefault, &qr);
    EncodeFn enc = (EncodeFn)fn;
    void *px, *po, *pw;
    cudaGetSymbolAddress(&px, g_x);
    cudaGetSymbolAddress(&po, g_o);
    cudaGetSymbolAddress(&pw, g_wkv);
    make_map(enc, &hs.mp.m[7], A_x, S_, D_);
    make_map(enc, &hs.mp.m[0], px, 3 * S_, D_);
    make_map(enc, &hs.mp.m[1], po, S_, D_);
    make_map(enc, &hs.mp.m[2], A_wqkv, D_, 1536);
    make_map(enc, &hs.mp.m[3], B_wq, D_, 512);
    make_map(enc, &hs.mp.m[4], pw, D_, 32);
    make_map(enc, &hs.mp.m[5], A_wo, D_, D_);
    make_map(enc, &hs.mp.m[6], B_wo, D_, D_);
    hs.mp.x0 = A_x; hs.mp.wqkv = A_wqkv; hs.mp.wq = B_wq; hs.mp.wk = B_wk;
    cudaFuncSetAttribute(prep_kernel, cudaFuncAttributePreferredSharedMemoryCarveout, 100);
    cudaFuncSetAttribute(g1a_kernel, cudaFuncAttributeMaxDynamicSharedMemorySize, G1A_SMEM);
    cudaFuncSetAttribute(mega_kernel, cudaFuncAttributeMaxDynamicSharedMemorySize, MEGA_SMEM);
    for (int i = 0; i < 8; i++) hs.in[i] = d_in[i];
    hs.init = true;
  }
  hs.mp.out = (__nv_bfloat16*)d_out;
  launch(prep_kernel, 130, 256, 0, false, A_x, A_wqkv, B_wq, B_wk, B_wv);
  launch(g1a_kernel, 128, 288, G1A_SMEM, true, hs.mp.m[7], hs.mp.m[2]);
  launch(mega_kernel, 128, 640, MEGA_SMEM, true, hs.mp);
}
```

```cpp
#include <cuda_runtime.h>
#include <cuda_bf16.h>
#include <cuda_fp16.h>
#include <cuda.h>
#include <stdint.h>

namespace {

constexpr int S_ = 2048, D_ = 512, H_ = 32;

__device__ __align__(1024) __nv_bfloat16 g_x[3 * S_ * D_];
__device__ __align__(1024) __nv_bfloat16 g_o[S_ * D_];
__device__ __align__(1024) uint4 g_q[2 * H_ * S_ * 2];
__device__ __align__(1024) uint4 g_k[2 * H_ * S_ * 2];
__device__ __align__(1024) uint4 g_v[2 * H_ * S_ * 2];
__device__ __align__(1024) __nv_bfloat16 g_wkv[D_ * 32];
__device__ __align__(16) float2 g_stats[4 * S_ * 8];
__device__ __align__(16) float g_colsum[1536 + 512 + 64];
__device__ float g_nrm[4 * 2 * H_ * 64];
constexpr int CNT_O = 0, CNT_X = 32, CNT_KV = CNT_X + 128, CNT_Q = CNT_KV + 64, CNT_DONE = CNT_Q + 256, CNT_N = CNT_DONE + 1;
__device__ unsigned g_cnt[CNT_N];

#define EXP_NIT 32
#define EXP_AUX 0
#define TM(k, slot)
#define TM1(k, slot)
#define TM2(k, slot)
#define TM3(k, slot)
__device__ __forceinline__ uint32_t s2u(const void* p) { return (uint32_t)__cvta_generic_to_shared(p); }
__device__ __forceinline__ void mbar_init(uint32_t bar, int cnt) {
  asm volatile("mbarrier.init.shared::cta.b64 [%0], %1;" ::"r"(bar), "r"(cnt) : "memory");
}
__device__ __forceinline__ void mbar_expect(uint32_t bar, uint32_t bytes) {
  asm volatile("mbarrier.arrive.expect_tx.shared::cta.b64 _, [%0], %1;" ::"r"(bar), "r"(bytes) : "memory");
}
__device__ __forceinline__ void mbar_arrive(uint32_t bar) {
  asm volatile("mbarrier.arrive.shared::cta.b64 _, [%0];" ::"r"(bar) : "memory");
}
__device__ __forceinline__ void mbar_wait(uint32_t bar, uint32_t par) {
  uint32_t ok;
  int it = 0;
  do {
    asm volatile("{.reg .pred p; mbarrier.try_wait.parity.shared::cta.b64 p, [%1], %2; selp.u32 %0,1,0,p;}"
                 : "=r"(ok) : "r"(bar), "r"(par) : "memory");
    if (++it > (1 << 24)) __trap();
  } while (!ok);
}
#define SLEEP_NS 32
__device__ __forceinline__ void mbar_wait_long(uint32_t bar, uint32_t par) {
  uint32_t ok;
  int it = 0;
  while (true) {
    asm volatile("{.reg .pred p; mbarrier.test_wait.parity.shared::cta.b64 p, [%1], %2; selp.u32 %0,1,0,p;}"
                 : "=r"(ok) : "r"(bar), "r"(par) : "memory");
    if (ok) break;
    if (++it > (1 << 24)) __trap();
    __nanosleep(SLEEP_NS);
  }
}
__device__ __forceinline__ void bulk_load(uint32_t dst, const void* src, uint32_t bytes, uint32_t bar) {
  asm volatile("cp.async.bulk.shared::cluster.global.mbarrier::complete_tx::bytes [%0], [%1], %2, [%3];"
               ::"r"(dst), "l"(src), "r"(bytes), "r"(bar) : "memory");
}
__device__ __forceinline__ void tma_load(uint32_t dst, const CUtensorMap* m, int c0, int c1, uint32_t bar) {
  asm volatile("cp.async.bulk.tensor.2d.shared::cluster.global.mbarrier::complete_tx::bytes [%0], [%1, {%3, %4}], [%2];"
               ::"r"(dst), "l"(m), "r"(bar), "r"(c0), "r"(c1) : "memory");
}
__device__ __forceinline__ bool elect_one() {
  uint32_t p;
  asm volatile("{.reg .pred q; elect.sync _|q, 0xffffffff; selp.u32 %0, 1, 0, q;}" : "=r"(p));
  return p;
}
__device__ __forceinline__ void pdl_wait() { asm volatile("griddepcontrol.wait;" ::: "memory"); }
__device__ __forceinline__ void pdl_launch() { asm volatile("griddepcontrol.launch_dependents;" ::: "memory"); }
__device__ __forceinline__ void fence_async_smem() { asm volatile("fence.proxy.async.shared::cta;" ::: "memory"); }
__device__ __forceinline__ void fence_bar_init() { asm volatile("fence.mbarrier_init.release.cluster;" ::: "memory"); }
__device__ __forceinline__ void named_sync(int id, int n) { asm volatile("bar.sync %0, %1;" ::"r"(id), "r"(n) : "memory"); }
__device__ __forceinline__ void wg_fence() { asm volatile("wgmma.fence.sync.aligned;" ::: "memory"); }
__device__ __forceinline__ void wg_commit() { asm volatile("wgmma.commit_group.sync.aligned;" ::: "memory"); }
template <int N> __device__ __forceinline__ void wg_wait() { asm volatile("wgmma.wait_group.sync.aligned %0;" ::"n"(N) : "memory"); }
template <int N> __device__ __forceinline__ void pin(float (&d)[N]) {
#pragma unroll
  for (int i = 0; i < N; i++) asm volatile("" : "+f"(d[i])::"memory");
}
template <int N> __device__ __forceinline__ void pin(uint32_t (&d)[N]) {
#pragma unroll
  for (int i = 0; i < N; i++) asm volatile("" : "+r"(d[i])::"memory");
}
__device__ __forceinline__ uint64_t mkdesc(uint32_t addr, uint32_t lbo, uint32_t sbo, uint64_t swz) {
  return (uint64_t)((addr & 0x3FFFF) >> 4) | ((uint64_t)(lbo >> 4) << 16) | ((uint64_t)(sbo >> 4) << 32) | (swz << 62);
}
__device__ __forceinline__ uint32_t pack_bf16(float lo, float hi) {
  uint32_t d; asm("cvt.rn.bf16x2.f32 %0, %1, %2;" : "=r"(d) : "f"(hi), "f"(lo)); return d;
}
__device__ __forceinline__ uint32_t pack_f16(float lo, float hi) {
  uint32_t d; asm("cvt.rn.f16x2.f32 %0, %1, %2;" : "=r"(d) : "f"(hi), "f"(lo)); return d;
}
__device__ __forceinline__ float bf_lo(uint32_t v) { return __uint_as_float(v << 16); }
__device__ __forceinline__ float bf_hi(uint32_t v) { return __uint_as_float(v & 0xffff0000u); }
__device__ __forceinline__ void stsm4(uint32_t addr, uint32_t a, uint32_t b, uint32_t c, uint32_t d) {
  asm volatile("stmatrix.sync.aligned.m8n8.x4.shared.b16 [%0], {%1,%2,%3,%4};" ::"r"(addr), "r"(a), "r"(b), "r"(c), "r"(d) : "memory");
}
__device__ __forceinline__ void ldsm4(uint32_t addr, uint32_t& a, uint32_t& b, uint32_t& c, uint32_t& d) {
  asm volatile("ldmatrix.sync.aligned.m8n8.x4.shared.b16 {%0,%1,%2,%3}, [%4];" : "=r"(a), "=r"(b), "=r"(c), "=r"(d) : "r"(addr) : "memory");
}
__device__ __forceinline__ uint32_t hadd2_bf16(uint32_t a, uint32_t b) {
  uint32_t d; asm("add.rn.bf16x2 %0, %1, %2;" : "=r"(d) : "r"(a), "r"(b)); return d;
}
__device__ __forceinline__ uint4 lds128(uint32_t addr) {
  uint4 v; asm volatile("ld.shared.v4.u32 {%0,%1,%2,%3}, [%4];" : "=r"(v.x), "=r"(v.y), "=r"(v.z), "=r"(v.w) : "r"(addr) : "memory"); return v;
}

__device__ __forceinline__ void wgmma_qk_n64(float (&d)[32], uint64_t da, uint64_t db) {
  asm volatile("wgmma.mma_async.sync.aligned.m64n64k16.f32.f16.f16 "
      "{%0,%1,%2,%3,%4,%5,%6,%7,%8,%9,%10,%11,%12,%13,%14,%15,%16,%17,%18,%19,%20,%21,%22,%23,%24,%25,%26,%27,%28,%29,%30,%31}, "
      "%32, %33, 1, 1, 1, 0, 0;"
    : "+f"(d[0]), "+f"(d[1]), "+f"(d[2]), "+f"(d[3]), "+f"(d[4]), "+f"(d[5]), "+f"(d[6]), "+f"(d[7]), "+f"(d[8]),
      "+f"(d[9]), "+f"(d[10]), "+f"(d[11]), "+f"(d[12]), "+f"(d[13]), "+f"(d[14]), "+f"(d[15]), "+f"(d[16]),
      "+f"(d[17]), "+f"(d[18]), "+f"(d[19]), "+f"(d[20]), "+f"(d[21]), "+f"(d[22]), "+f"(d[23]), "+f"(d[24]),
      "+f"(d[25]), "+f"(d[26]), "+f"(d[27]), "+f"(d[28]), "+f"(d[29]), "+f"(d[30]), "+f"(d[31])
    : "l"(da), "l"(db));
}
__device__ __forceinline__ void wgmma_pv_n24(float (&d)[12], uint32_t a0, uint32_t a1, uint32_t a2, uint32_t a3, uint64_t db) {
  asm volatile("wgmma.mma_async.sync.aligned.m64n24k16.f32.bf16.bf16 "
      "{%0,%1,%2,%3,%4,%5,%6,%7,%8,%9,%10,%11}, "
      "{%12,%13,%14,%15}, %16, 1, 1, 1, 1;"
    : "+f"(d[0]), "+f"(d[1]), "+f"(d[2]), "+f"(d[3]), "+f"(d[4]), "+f"(d[5]), "+f"(d[6]), "+f"(d[7]), "+f"(d[8]),
      "+f"(d[9]), "+f"(d[10]), "+f"(d[11])
    : "r"(a0), "r"(a1), "r"(a2), "r"(a3), "l"(db));
}
__device__ __forceinline__ void wgmma_gemm_n64(float (&d)[32], uint64_t da, uint64_t db) {
  asm volatile("wgmma.mma_async.sync.aligned.m64n64k16.f32.bf16.bf16 "
      "{%0,%1,%2,%3,%4,%5,%6,%7,%8,%9,%10,%11,%12,%13,%14,%15,%16,%17,%18,%19,%20,%21,%22,%23,%24,%25,%26,%27,%28,%29,%30,%31}, "
      "%32, %33, 1, 1, 1, 0, 1;"
    : "+f"(d[0]), "+f"(d[1]), "+f"(d[2]), "+f"(d[3]), "+f"(d[4]), "+f"(d[5]), "+f"(d[6]), "+f"(d[7]), "+f"(d[8]),
      "+f"(d[9]), "+f"(d[10]), "+f"(d[11]), "+f"(d[12]), "+f"(d[13]), "+f"(d[14]), "+f"(d[15]), "+f"(d[16]),
      "+f"(d[17]), "+f"(d[18]), "+f"(d[19]), "+f"(d[20]), "+f"(d[21]), "+f"(d[22]), "+f"(d[23]), "+f"(d[24]),
      "+f"(d[25]), "+f"(d[26]), "+f"(d[27]), "+f"(d[28]), "+f"(d[29]), "+f"(d[30]), "+f"(d[31])
    : "l"(da), "l"(db));
}
__device__ __forceinline__ void wgmma_gemm_n32(float (&d)[16], uint64_t da, uint64_t db) {
  asm volatile("wgmma.mma_async.sync.aligned.m64n32k16.f32.bf16.bf16 "
      "{%0,%1,%2,%3,%4,%5,%6,%7,%8,%9,%10,%11,%12,%13,%14,%15}, "
      "%16, %17, 1, 1, 1, 0, 1;"
    : "+f"(d[0]), "+f"(d[1]), "+f"(d[2]), "+f"(d[3]), "+f"(d[4]), "+f"(d[5]), "+f"(d[6]), "+f"(d[7]), "+f"(d[8]),
      "+f"(d[9]), "+f"(d[10]), "+f"(d[11]), "+f"(d[12]), "+f"(d[13]), "+f"(d[14]), "+f"(d[15])
    : "l"(da), "l"(db));
}
__device__ __forceinline__ void wgmma_gemm_n192(float (&d)[96], uint64_t da, uint64_t db) {
  asm volatile("wgmma.mma_async.sync.aligned.m64n192k16.f32.bf16.bf16 "
      "{%0,%1,%2,%3,%4,%5,%6,%7,%8,%9,%10,%11,%12,%13,%14,%15,%16,%17,%18,%19,%20,%21,%22,%23,%24,%25,%26,%27,%28,%29,%30,%31,%32,%33,%34,%35,%36,%37,%38,%39,%40,%41,%42,%43,%44,%45,%46,%47,%48,%49,%50,%51,%52,%53,%54,%55,%56,%57,%58,%59,%60,%61,%62,%63,%64,%65,%66,%67,%68,%69,%70,%71,%72,%73,%74,%75,%76,%77,%78,%79,%80,%81,%82,%83,%84,%85,%86,%87,%88,%89,%90,%91,%92,%93,%94,%95}, "
      "%96, %97, 1, 1, 1, 0, 1;"
    : "+f"(d[0]), "+f"(d[1]), "+f"(d[2]), "+f"(d[3]), "+f"(d[4]), "+f"(d[5]), "+f"(d[6]), "+f"(d[7]), "+f"(d[8]),
      "+f"(d[9]), "+f"(d[10]), "+f"(d[11]), "+f"(d[12]), "+f"(d[13]), "+f"(d[14]), "+f"(d[15]), "+f"(d[16]),
      "+f"(d[17]), "+f"(d[18]), "+f"(d[19]), "+f"(d[20]), "+f"(d[21]), "+f"(d[22]), "+f"(d[23]), "+f"(d[24]),
      "+f"(d[25]), "+f"(d[26]), "+f"(d[27]), "+f"(d[28]), "+f"(d[29]), "+f"(d[30]), "+f"(d[31]), "+f"(d[32]),
      "+f"(d[33]), "+f"(d[34]), "+f"(d[35]), "+f"(d[36]), "+f"(d[37]), "+f"(d[38]), "+f"(d[39]), "+f"(d[40]),
      "+f"(d[41]), "+f"(d[42]), "+f"(d[43]), "+f"(d[44]), "+f"(d[45]), "+f"(d[46]), "+f"(d[47]), "+f"(d[48]),
      "+f"(d[49]), "+f"(d[50]), "+f"(d[51]), "+f"(d[52]), "+f"(d[53]), "+f"(d[54]), "+f"(d[55]), "+f"(d[56]),
      "+f"(d[57]), "+f"(d[58]), "+f"(d[59]), "+f"(d[60]), "+f"(d[61]), "+f"(d[62]), "+f"(d[63]), "+f"(d[64]),
      "+f"(d[65]), "+f"(d[66]), "+f"(d[67]), "+f"(d[68]), "+f"(d[69]), "+f"(d[70]), "+f"(d[71]), "+f"(d[72]),
      "+f"(d[73]), "+f"(d[74]), "+f"(d[75]), "+f"(d[76]), "+f"(d[77]), "+f"(d[78]), "+f"(d[79]), "+f"(d[80]),
      "+f"(d[81]), "+f"(d[82]), "+f"(d[83]), "+f"(d[84]), "+f"(d[85]), "+f"(d[86]), "+f"(d[87]), "+f"(d[88]),
      "+f"(d[89]), "+f"(d[90]), "+f"(d[91]), "+f"(d[92]), "+f"(d[93]), "+f"(d[94]), "+f"(d[95])
    : "l"(da), "l"(db));
}

constexpr float QSCALE = 0.25f * 1.4426950408889634f;
constexpr float LN_EPS = 1e-5f;

__device__ __forceinline__ void row_stats(int layer, int row, float& mu, float& rstd) {
  const float4* p = reinterpret_cast<const float4*>(g_stats + (layer * S_ + row) * 8);
  float4 a = __ldcg(p), b = __ldcg(p + 1), c = __ldcg(p + 2), d = __ldcg(p + 3);
  float s = (a.x + a.z) + (b.x + b.z) + (c.x + c.z) + (d.x + d.z);
  float q = (a.y + a.w) + (b.y + b.w) + (c.y + c.w) + (d.y + d.w);
  mu = s * (1.f / D_);
  float var = fmaxf(q * (1.f / D_) - mu * mu, 0.f);
  rstd = rsqrtf(var + LN_EPS);
}

__global__ void __launch_bounds__(256) prep_kernel(const __nv_bfloat16* __restrict__ x, const __nv_bfloat16* __restrict__ wqkv,
                                                   const __nv_bfloat16* __restrict__ wq, const __nv_bfloat16* __restrict__ wk,
                                                   const __nv_bfloat16* __restrict__ wv) {
  TM(0, 0);
  pdl_launch();
  __shared__ float red[8][16];
  const int b = blockIdx.x, tid = threadIdx.x, lane = tid & 31, warp = tid >> 5;
  {
    const __nv_bfloat16* w; int ld, out;
    if (b < 96) { w = wqkv + b * 16; ld = 1536; out = b * 16; }
    else if (b < 128) { w = wq + (b - 96) * 16; ld = 512; out = 1536 + (b - 96) * 16; }
    else { w = (b == 128) ? wk : wv; ld = 16; out = 2048 + (b - 128) * 16; }
    const int half = tid & 1, r0 = tid >> 1;
    float acc[8];
#pragma unroll
    for (int i = 0; i < 8; i++) acc[i] = 0.f;
#pragma unroll
    for (int j = 0; j < 4; j++) {
      uint4 v = __ldg(reinterpret_cast<const uint4*>(w + (size_t)(r0 + 128 * j) * ld + half * 8));
      if (b >= 128) *reinterpret_cast<uint4*>(g_wkv + (r0 + 128 * j) * 32 + (b - 128) * 16 + half * 8) = v;
      acc[0] += bf_lo(v.x); acc[1] += bf_hi(v.x); acc[2] += bf_lo(v.y); acc[3] += bf_hi(v.y);
      acc[4] += bf_lo(v.z); acc[5] += bf_hi(v.z); acc[6] += bf_lo(v.w); acc[7] += bf_hi(v.w);
    }
#pragma unroll
    for (int i = 0; i < 8; i++) {
#pragma unroll
      for (int o = 2; o < 32; o <<= 1) acc[i] += __shfl_xor_sync(0xffffffffu, acc[i], o);
    }
    if (lane < 2) {
#pragma unroll
      for (int i = 0; i < 8; i++) red[warp][lane * 8 + i] = acc[i];
    }
    __syncthreads();
    if (tid < 16) {
      float s = 0.f;
#pragma unroll
      for (int w8 = 0; w8 < 8; w8++) s += red[w8][tid];
      g_colsum[out + tid] = s;
    }
    if (b == 129 && tid >= 32 && tid < 64) g_colsum[2048 + tid] = 0.f;
  }
  if (b < 128) {
#pragma unroll
    for (int j = 0; j < 2; j++) {
      const int row = b * 16 + warp * 2 + j;
      const uint4* p = reinterpret_cast<const uint4*>(x + (size_t)row * D_ + lane * 16);
      uint4 v0 = __ldg(p), v1 = __ldg(p + 1);
      uint32_t u[8] = {v0.x, v0.y, v0.z, v0.w, v1.x, v1.y, v1.z, v1.w};
      float s = 0.f, q = 0.f;
#pragma unroll
      for (int i = 0; i < 8; i++) {
        float a = bf_lo(u[i]), c = bf_hi(u[i]);
        s += a + c; q = fmaf(a, a, fmaf(c, c, q));
      }
      s += __shfl_xor_sync(0xffffffffu, s, 1); q += __shfl_xor_sync(0xffffffffu, q, 1);
      s += __shfl_xor_sync(0xffffffffu, s, 2); q += __shfl_xor_sync(0xffffffffu, q, 2);
      if ((lane & 3) == 0) g_stats[row * 8 + (lane >> 2)] = make_float2(s, q);
    }
  }
  TM(0, 4);
}

__device__ __forceinline__ int tok0(int r, int rb) { return (rb >> 2) * 512 + r * 256 + (rb & 3) * 64; }
__device__ __forceinline__ int key_pos(int token) {
  const int r = (token >> 8) & 1, rb = ((token >> 9) << 2) | ((token >> 6) & 3), row = token & 63;
  return (16 * r + (row >> 2)) * 64 + rb * 4 + (row & 3);
}
__device__ __forceinline__ float sq_norm16(const uint4& a, const uint4& b) {
  const uint32_t u[8] = {a.x, a.y, a.z, a.w, b.x, b.y, b.z, b.w};
  __half2 n = __hmul2(*reinterpret_cast<const __half2*>(&u[0]), *reinterpret_cast<const __half2*>(&u[0]));
#pragma unroll
  for (int i = 1; i < 8; i++) n = __hfma2(*reinterpret_cast<const __half2*>(&u[i]), *reinterpret_cast<const __half2*>(&u[i]), n);
  return __low2float(n) + __high2float(n);
}
__device__ __forceinline__ uint32_t hsub2(uint32_t a, uint32_t b) {
  uint32_t d; asm("sub.rn.f16x2 %0, %1, %2;" : "=r"(d) : "r"(a), "r"(b)); return d;
}
__device__ __forceinline__ void proj_store(uint32_t a, uint32_t ap, int type, int layer, int head, int token) {
  const uint4 v0 = lds128(a), v1 = lds128(a + 16);
  const size_t hb = (size_t)((layer & 1) * H_ + head) * (S_ * 2);
  if (type == 2) {
    uint4* dst = g_v + hb + key_pos(token);
    dst[0] = v0; dst[S_] = v1;
    return;
  }
  if (type == 0) {
    uint4* dst = g_q + hb + (token >> 3) * 16 + (token & 7);
    dst[0] = v0; dst[8] = v1;
  } else {
    uint4 d0 = v0, d1 = v1;
    if (ap) {
      const uint4 p0 = lds128(ap), p1 = lds128(ap + 16);
      d0 = make_uint4(hsub2(v0.x, p0.x), hsub2(v0.y, p0.y), hsub2(v0.z, p0.z), hsub2(v0.w, p0.w));
      d1 = make_uint4(hsub2(v1.x, p1.x), hsub2(v1.y, p1.y), hsub2(v1.z, p1.z), hsub2(v1.w, p1.w));
    }
    const int pos = key_pos(token);
    uint4* dst = g_k + hb + (pos >> 3) * 16 + (pos & 7);
    dst[0] = d0; dst[8] = d1;
  }
  const unsigned m = __reduce_max_sync(0xffffffffu, __float_as_uint(sq_norm16(v0, v1)) & 0x7fffffffu);
  if ((threadIdx.x & 31) == 0) g_nrm[((layer * 2 + type) * H_ + head) * 64 + (token >> 5)] = __uint_as_float(m);
}
template <bool F16, int N>
__device__ __forceinline__ void proj_stage(const float (&acc)[N], int j  , uint32_t addr, const float* cs,
                                           float mu0, float f0, float mu1, float f1) {
  uint32_t r[4];
#pragma unroll
  for (int e = 0; e < 2; e++) {
    const float2 c = *reinterpret_cast<const float2*>(cs + (j + e) * 8);
    const float a0 = fmaf(-mu0, c.x, acc[(j + e) * 4 + 0]) * f0, a1 = fmaf(-mu0, c.y, acc[(j + e) * 4 + 1]) * f0;
    const float a2 = fmaf(-mu1, c.x, acc[(j + e) * 4 + 2]) * f1, a3 = fmaf(-mu1, c.y, acc[(j + e) * 4 + 3]) * f1;
    r[e * 2] = F16 ? pack_f16(a0, a1) : pack_bf16(a0, a1);
    r[e * 2 + 1] = F16 ? pack_f16(a2, a3) : pack_bf16(a2, a3);
  }
  stsm4(addr + j * 16, r[0], r[1], r[2], r[3]);
}

constexpr int G1A_NS = 5, G1A_STAGE = 16384 + 3 * 8192, G1A_PITCH = 400;
constexpr int G1A_SMEM = G1A_NS * G1A_STAGE + 1024 + 192 * 4 + 128;
__global__ void __launch_bounds__(288, 1) g1a_kernel(const __grid_constant__ CUtensorMap mx, const __grid_constant__ CUtensorMap mw) {
  extern __shared__ uint8_t smem_raw[];
  const uint32_t sbase = (s2u(smem_raw) + 1023) & ~1023u;
  const uint32_t s_cs = sbase + G1A_NS * G1A_STAGE, s_bar = s_cs + 192 * 4;
  float* cs = reinterpret_cast<float*>(smem_raw + (s_cs - s2u(smem_raw)));
  const int tid = threadIdx.x, warp = tid >> 5, lane = tid & 31;
  const int nb = blockIdx.x & 7, rb = blockIdx.x >> 3;
  TM(1, 0);
  if (tid == 0) {
    for (int i = 0; i < G1A_NS; i++) { mbar_init(s_bar + i * 8, 1); mbar_init(s_bar + 40 + i * 8, 2); }
    fence_bar_init();
  }
  __syncthreads();
  if (warp == 8) {
    if (lane == 0) {
      for (int c = 0; c < 8; c++) {
        const int s = c < G1A_NS ? c : c - G1A_NS;
        const uint32_t st = sbase + s * G1A_STAGE, bar = s_bar + s * 8;
        if (c >= G1A_NS) mbar_wait(s_bar + 40 + s * 8, 0);
        mbar_expect(bar, G1A_STAGE);
        tma_load(st, &mx, c * 64, tok0(0, rb), bar);
        tma_load(st + 8192, &mx, c * 64, tok0(1, rb), bar);
        for (int j = 0; j < 3; j++) tma_load(st + 16384 + j * 8192, &mw, nb * 192 + j * 64, c * 64, bar);
      }
    }
    return;
  }
  const int wg = warp >> 2;
  float acc[96];
#pragma unroll
  for (int i = 0; i < 96; i++) acc[i] = 0.f;
  pin(acc);
#pragma unroll 1
  for (int c = 0; c < 8; c++) {
    const int s = c < G1A_NS ? c : c - G1A_NS;
    mbar_wait(s_bar + s * 8, c >= G1A_NS);
    if (c == 0) TM(1, 2);
    const uint32_t st = sbase + s * G1A_STAGE;
    const uint64_t da = mkdesc(st + wg * 8192, 16, 1024, 1), db = mkdesc(st + 16384, 8192, 1024, 1);
    wg_fence();
#pragma unroll
    for (int k = 0; k < 4; k++) wgmma_gemm_n192(acc, da + k * 2, db + k * 128);
    wg_commit();
    if (c >= 1 && c <= 3) { wg_wait<1>(); if ((tid & 127) == 0) mbar_arrive(s_bar + 40 + (c - 1) * 8); }
    if (c == 5) {
      pdl_wait();
      pdl_launch();
      if (tid < 192) cs[tid] = __ldcg(g_colsum + nb * 192 + tid);
    }
  }
  float mu0, rs0, mu1, rs1;
  const int row0 = tok0(wg, rb) + (warp & 3) * 16 + (lane >> 2);
  row_stats(0, row0, mu0, rs0); row_stats(0, row0 + 8, mu1, rs1);
  wg_wait<0>();
  pin(acc);
  TM(1, 3);
  named_sync(1, 256);
  {
    const uint32_t addr = sbase + (wg * 64 + (warp & 3) * 16 + (lane & 15)) * G1A_PITCH + (lane >> 4) * 16;
#pragma unroll
    for (int j = 0; j < 24; j += 2) {
      const int type = (nb * 12 + (j >> 1)) >> 5;
      const float sc = type == 0 ? QSCALE : 1.f;
      if (type == 2) proj_stage<false>(acc, j, addr, cs + (lane & 3) * 2, mu0, rs0, mu1, rs1);
      else proj_stage<true>(acc, j, addr, cs + (lane & 3) * 2, mu0, rs0 * sc, mu1, rs1 * sc);
    }
  }
  named_sync(1, 256);
#pragma unroll
  for (int it = 0; it < 6; it++) {
    const int item = warp + it * 8, hh = item >> 2, trow = (item & 3) * 32 + lane;
    const int hg = nb * 12 + hh;
    const uint32_t a = sbase + trow * G1A_PITCH + hh * 32;
    proj_store(a, trow >= 4 ? a - 4 * G1A_PITCH : 0u, hg >> 5, 0, hg & 31, tok0(trow >> 6, rb) + (trow & 63));
  }
  TM(1, 4);
}

constexpr uint32_t MUFU_MASK = 0xF800u;
constexpr float EXP_MAGIC = 383.0f + 0.65f / 128.0f;
constexpr uint32_t POLY_A = 0x5a835a83u, POLY_B = 0x92a192a1u, POLY_C = 0x800b800bu;
constexpr float SCORE_LIMIT = 116.f;

__device__ __forceinline__ void exp_step(const float (&s)[32], uint32_t (&p)[16], uint32_t pb) {
#pragma unroll
  for (int i = 0; i < 16; i++) {
    if ((MUFU_MASK >> i) & 1) {
      float a, b;
      asm("ex2.approx.ftz.f32 %0, %1;" : "=f"(a) : "f"(s[2 * i]));
      asm("ex2.approx.ftz.f32 %0, %1;" : "=f"(b) : "f"(s[2 * i + 1]));
      p[i] = pack_bf16(a, b);
    } else {
      uint32_t z, u, h;
      asm("prmt.b32 %0, %1, %2, 0x6521;" : "=r"(z) : "r"(__float_as_uint(s[2 * i])), "r"(__float_as_uint(s[2 * i + 1])));
      asm("fma.rn.f16x2 %0, %1, %2, %3;" : "=r"(u) : "r"(z & 0x007f007fu), "r"(POLY_A), "r"(pb));
      asm("fma.rn.f16x2 %0, %1, %1, %2;" : "=r"(h) : "r"(u), "r"(POLY_C));
      p[i] = z - h;
    }
  }
}

__device__ __forceinline__ void pv4(float (&o)[12], const uint32_t (&p)[16], uint64_t dv) {
#pragma unroll
  for (int j = 0; j < 4; j++) wgmma_pv_n24(o, p[4 * j], p[4 * j + 1], p[4 * j + 2], p[4 * j + 3], dv + j * 16);
}
template <bool PV>
__device__ __forceinline__ void att_step(float (&s)[32], float (&o)[12], uint32_t (&pin_)[16], uint32_t (&pout)[16], uint64_t dq,
                                         uint64_t dk, uint64_t dv, uint32_t pb) {
  pin(s);
  if (PV) pin(pin_);
  wg_fence();
  wgmma_qk_n64(s, dq, dk);
  wg_commit();
  if (PV) {
#pragma unroll
    for (int j = 0; j < 4; j++) wgmma_pv_n24(o, pin_[4 * j], pin_[4 * j + 1], pin_[4 * j + 2], pin_[4 * j + 3], dv + j * 16);
    wg_commit();
    wg_wait<1>();
  } else {
    wg_wait<0>();
  }
  pin(s);
  exp_step(s, pout, pb);
  pin(pout);
}

constexpr int M_STAGE = 0;
constexpr int M_STG = 65536, STG_PITCH = 144;
constexpr int M_KV = 74752;
constexpr int M_Q = M_KV + 17 * 8192;
constexpr int M_CS = M_Q + 16384, M_KTAIL = M_CS + 768, M_ROW = M_KTAIL + 512, M_BAR = M_ROW + 512;
constexpr int MEGA_SMEM = M_BAR + 256;
__device__ __forceinline__ int k_unit(int b, int j) { return j == 0 ? 12 - 4 * b : 7 - 2 * b; }
__device__ __forceinline__ int v_unit(int b, int j) { return j == 0 ? 14 - 4 * b : 15 - 2 * b; }
constexpr int B_FULL = 0, B_EMPTY = 32, B_KV = 64, B_Q = 80, B_FREE0 = 96, B_ODONE = 104, B_RES = 120, B_PRE = 128,
              B_TURN = 136, B_EPI = 168, B_CHK = 200, M_CHK = M_BAR + 208;

struct MegaParams {
  CUtensorMap m[8];
  const __nv_bfloat16* x0;
  const __nv_bfloat16* wqkv; const __nv_bfloat16* wq; const __nv_bfloat16* wk;
  __nv_bfloat16* out;
};

__device__ __forceinline__ void cnt_signal(int idx) {
  if (elect_one()) asm volatile("red.release.gpu.global.add.u32 [%0], 1;" ::"l"(g_cnt + idx) : "memory");
}
__device__ __forceinline__ void cnt_wait(int idx, unsigned target) {
  unsigned v;
  int it = 0;
  while (true) {
    asm volatile("ld.acquire.gpu.global.u32 %0, [%1];" : "=r"(v) : "l"(g_cnt + idx) : "memory");
    if (v >= target) break;
    if (++it > (1 << 24)) __trap();
    __nanosleep(40);
  }
  asm volatile("fence.proxy.async.global;" ::: "memory");
}

__device__ __forceinline__ void att_fallback(const MegaParams& P, int layer, int head, int row0, __nv_bfloat16* sk, int bar_id) {
  int t;
  asm volatile("mov.u32 %0, %%tid.x;" : "=r"(t));
  t &= 127;
  const int hf = t & 1;
  asm volatile("" : "+r"(layer), "+r"(head), "+r"(row0));
  const __nv_bfloat16* x = layer == 0 ? P.x0 : g_x + (size_t)(layer - 1) * S_ * D_;
  const bool mqa = layer & 1;
  const __nv_bfloat16* vimg = reinterpret_cast<const __nv_bfloat16*>(g_v + (size_t)((layer & 1) * H_ + (mqa ? 0 : head)) * (S_ * 2));
  float q[16], o[16], acc[16];
  float m = -INFINITY, l = 0.f;
#pragma unroll
  for (int d = 0; d < 16; d++) { o[d] = 0.f; q[d] = 0.f; }
#pragma unroll 1
  for (int ch = -1; ch < 32; ch++) {
    const int token = ch < 0 ? row0 + (t >> 1) : ch * 64 + (t >> 1);
    const __nv_bfloat16* w = ch < 0 ? (mqa ? P.wq : P.wqkv) + head * 16 : (mqa ? P.wk : P.wqkv + 512 + head * 16);
    const int ld = mqa ? (ch < 0 ? 512 : 16) : 1536;
    float mu, rs;
    row_stats(layer, token, mu, rs);
#pragma unroll
    for (int d = 0; d < 16; d++) acc[d] = 0.f;
#pragma unroll 1
    for (int k = hf * 256; k < hf * 256 + 256; k++) {
      const unsigned short xr = __ldcg(reinterpret_cast<const unsigned short*>(x) + (size_t)token * D_ + k);
      const float xn = __bfloat162float(__float2bfloat16((__uint_as_float((uint32_t)xr << 16) - mu) * rs));
#pragma unroll
      for (int d = 0; d < 16; d++) acc[d] = fmaf(xn, __bfloat162float(w[(size_t)k * ld + d]), acc[d]);
    }
#pragma unroll
    for (int d = 0; d < 16; d++) acc[d] = __bfloat162float(__float2bfloat16(acc[d] + __shfl_xor_sync(0xffffffffu, acc[d], 1)));
    if (ch < 0) {
#pragma unroll
      for (int d = 0; d < 16; d++) q[d] = acc[d];
      continue;
    }
    named_sync(bar_id, 128);
    if (hf == 0) {
#pragma unroll
      for (int d = 0; d < 16; d++) sk[(t >> 1) * 16 + d] = __float2bfloat16(acc[d]);
    }
    named_sync(bar_id, 128);
#pragma unroll 1
    for (int j = hf * 32; j < hf * 32 + 32; j++) {
      float sc = 0.f;
#pragma unroll
      for (int d = 0; d < 16; d++) sc = fmaf(q[d], __bfloat162float(sk[j * 16 + d]), sc);
      sc *= 0.25f;
      if (sc > m || sc != sc) {
        const float a = __expf(m - sc);
        l *= a;
#pragma unroll
        for (int d = 0; d < 16; d++) o[d] *= a;
        m = sc;
      }
      const float p = __expf(sc - m);
      l += p;
      const int pos = key_pos(ch * 64 + j);
#pragma unroll
      for (int d = 0; d < 16; d++) {
        const unsigned short vr = __ldcg(reinterpret_cast<const unsigned short*>(vimg) + (d >> 3) * (S_ * 8) + pos * 8 + (d & 7));
        o[d] = fmaf(p, __uint_as_float((uint32_t)vr << 16), o[d]);
      }
    }
  }
  const float m2 = __shfl_xor_sync(0xffffffffu, m, 1), mm = fmaxf(m, m2), a = __expf(m - mm);
  l *= a; l += __shfl_xor_sync(0xffffffffu, l, 1);
  const float inv = 1.f / l;
  __nv_bfloat16* dst = g_o + (size_t)(row0 + (t >> 1)) * D_ + head * 16;
#pragma unroll
  for (int d = 0; d < 16; d++) {
    float v = o[d] * a; v += __shfl_xor_sync(0xffffffffu, v, 1);
    if ((d >> 3) == hf) dst[d] = __float2bfloat16(v * inv);
  }
}

__device__ __forceinline__ const CUtensorMap* b_map(const MegaParams& P, int code) {
  const int l = code >> 3, p = code & 3;
  return &P.m[p == 0 ? 5 + (l & 1) : ((l & 1) ? 2 : (p == 3 ? 3 : 4))];
}
__device__ __forceinline__ int b_col(int code) {
  const int p = code & 3, ct = blockIdx.x & 7;
  return p == 0 || p == 3 ? ct * 64 : ((code & 8) ? p * 512 + ct * 64 : 0);
}
__device__ __forceinline__ void issue_b(uint32_t sbase, const CUtensorMap* m, int col, int st, int c) {
  mbar_expect(sbase + M_BAR + B_FULL + st * 8, 16384);
  tma_load(sbase + M_STAGE + st * 16384 + 8192, m, col, c * 64, sbase + M_BAR + B_FULL + st * 8);
}
__device__ __forceinline__ void issue_a(uint32_t sbase, const CUtensorMap* m, int row, int st, int c) {
  tma_load(sbase + M_STAGE + st * 16384, m, c * 64, row, sbase + M_BAR + B_FULL + st * 8);
}
__device__ __forceinline__ void load_kv(uint32_t sbase, int l, int r) {
  const size_t hb = (size_t)((l & 1) * H_ + ((l & 1) ? 0 : blockIdx.x >> 2)) * 65536;
  const uint8_t* gk = reinterpret_cast<const uint8_t*>(g_k) + hb;
  const uint8_t* gv = reinterpret_cast<const uint8_t*>(g_v) + hb;
  const uint32_t bar = sbase + M_BAR + B_KV + r * 8;
  if (elect_one()) {
    mbar_expect(bar, 65536);
#pragma unroll
    for (int j = 0; j < 2; j++) {
      const int b = r * 2 + j;
      bulk_load(sbase + M_KV + k_unit(b, 0) * 8192, gk + b * 16384, 8192, bar);
      bulk_load(sbase + M_KV + v_unit(b, 0) * 8192, gv + b * 8192, 8192, bar);
      bulk_load(sbase + M_KV + v_unit(b, 1) * 8192, gv + 32768 + b * 8192, 8192, bar);
      bulk_load(sbase + M_KV + k_unit(b, 1) * 8192, gk + b * 16384 + 8192, 8192, bar);
    }
  }
}
__device__ __forceinline__ void load_q(uint32_t sbase, int l, int r) {
  const uint32_t bar = sbase + M_BAR + B_Q + r * 8;
  if (elect_one()) {
    mbar_expect(bar, 8192);
    bulk_load(sbase + M_Q + r * 8192,
              reinterpret_cast<const uint8_t*>(g_q) + (size_t)((l & 1) * H_ + (blockIdx.x >> 2)) * 65536 + (blockIdx.x & 3) * 16384 + r * 8192,
              8192, bar);
  }
}

__device__ __forceinline__ bool pass_exists(int job, int p) {
  return p == 0 || (job < 6 && (p == 3 || (job & 2) || (p == 1 && (blockIdx.x & 7) == 0)));
}
__device__ __forceinline__ int next_pass(int code) {
  const int job = code >> 2, p = code & 3;
  if (p == 0 && pass_exists(job, 1)) return code + 1;
  if (p == 1 && pass_exists(job, 2)) return code + 1;
  if (p < 3 && pass_exists(job, 3)) return job * 4 + 3;
  return job * 4 + 4;
}
__device__ __forceinline__ int prev_pass(int code) {
  const int job = code >> 2, p = code & 3;
  if (p == 0) return job > 6 ? (job - 1) * 4 : (job - 1) * 4 + 3;
  if (p == 3 && pass_exists(job, 2)) return code - 1;
  if (p >= 2 && pass_exists(job, 1)) return job * 4 + 1;
  return job * 4;
}

__device__ __forceinline__ void proj_pass(const MegaParams& P, uint8_t* sm, uint32_t sbase, int code, int wg) {
  const uint32_t s_bar = sbase + M_BAR;
  const int prev = prev_pass(code);
  if (code > 0) mbar_wait_long(s_bar + B_TURN + (prev & 3) * 8, (prev >> 2) & 1);
  float acc[32];
#pragma unroll
  for (int i = 0; i < 32; i++) acc[i] = 0.f;
  pin(acc);
#pragma unroll
  for (int c = 0; c < 8; c++) {
    const uint32_t st = sbase + M_STAGE + (c & 3) * 16384;
    mbar_wait(s_bar + B_FULL + (c & 3) * 8, c >> 2);
    const uint64_t da = mkdesc(st, 16, 1024, 1), db = mkdesc(st + 8192, 8192, 1024, 1);
    wg_fence();
#pragma unroll
    for (int k = 0; k < 4; k++) wgmma_gemm_n64(acc, da + k * 2, db + k * 128);
    wg_commit();
    if (c & 3) {
      wg_wait<1>();
      if (elect_one()) mbar_arrive(s_bar + B_EMPTY + ((c - 1) & 3) * 8);
    }
    if (c == 3) {
      wg_wait<0>();
      if (elect_one()) mbar_arrive(s_bar + B_EMPTY + 24);
    }
  }
  wg_wait<0>();
  pin(acc);
  if (elect_one()) { mbar_arrive(s_bar + B_EMPTY + 24); mbar_arrive(s_bar + B_TURN + (code & 3) * 8); }
  int t;
  asm volatile("mov.u32 %0, %%tid.x;" : "=r"(t));
  t &= 127;
  const int lane = t & 31, w4 = t >> 5;
  const int l = code >> 3, r = (code >> 2) & 1, p = code & 3;
  const int rb = blockIdx.x >> 3, ct = blockIdx.x & 7, row0 = tok0(r, rb);
  const uint32_t stg = sbase + M_STG;
  if (p == 0) {
    mbar_wait(s_bar + B_RES, r);
    const uint32_t ra = stg + (w4 * 16 + (lane & 15)) * 128;
    float s0 = 0.f, q0 = 0.f, s1 = 0.f, q1 = 0.f;
#pragma unroll
    for (int j = 0; j < 8; j += 2) {
      const uint32_t a = ra + (((j + (lane >> 4)) ^ (lane & 7)) << 4);
      uint32_t y[4];
      ldsm4(a, y[0], y[1], y[2], y[3]);
#pragma unroll
      for (int e = 0; e < 4; e++) {
        y[e] = hadd2_bf16(y[e], pack_bf16(acc[4 * j + 2 * e], acc[4 * j + 2 * e + 1]));
        const float lo = bf_lo(y[e]), hi = bf_hi(y[e]);
        if (e & 1) { s1 += lo + hi; q1 = fmaf(lo, lo, fmaf(hi, hi, q1)); }
        else { s0 += lo + hi; q0 = fmaf(lo, lo, fmaf(hi, hi, q0)); }
      }
      stsm4(a, y[0], y[1], y[2], y[3]);
    }
    __syncwarp();
    __nv_bfloat16* xout = (l == 3 ? P.out : g_x + (size_t)l * S_ * D_) + (size_t)(row0 + w4 * 16 + (lane >> 3)) * D_ + ct * 64 + (lane & 7) * 8;
#pragma unroll
    for (int i = 0; i < 4; i++) {
      const int rr = i * 4 + (lane >> 3);
      *reinterpret_cast<uint4*>(xout + (size_t)i * 4 * D_) = lds128(stg + (w4 * 16 + rr) * 128 + (((lane & 7) ^ (rr & 7)) << 4));
    }
    if (l < 3) {
#pragma unroll
      for (int o = 1; o < 4; o <<= 1) {
        s0 += __shfl_xor_sync(0xffffffffu, s0, o); q0 += __shfl_xor_sync(0xffffffffu, q0, o);
        s1 += __shfl_xor_sync(0xffffffffu, s1, o); q1 += __shfl_xor_sync(0xffffffffu, q1, o);
      }
      if ((lane & 3) == 0) {
        float2* st = g_stats + ((l + 1) * S_ + row0 + w4 * 16 + (lane >> 2)) * 8 + ct;
        st[0] = make_float2(s0, q0); st[64] = make_float2(s1, q1);
      }
    }
  } else {
    const bool kv = !(l & 1) && p == 1;
    const int type = p == 3 ? 0 : p;
    mbar_wait(s_bar + B_PRE, r);
    mbar_wait(s_bar + B_EPI + (prev & 3) * 8, (prev >> 2) & 1);
    const float2 st0 = reinterpret_cast<const float2*>(sm + M_ROW)[w4 * 16 + (lane >> 2)];
    const float2 st1 = reinterpret_cast<const float2*>(sm + M_ROW)[w4 * 16 + (lane >> 2) + 8];
    const float* cs = reinterpret_cast<const float*>(sm + M_CS) + (p - 1) * 64 + (lane & 3) * 2;
    const uint32_t saddr = stg + (w4 * 16 + (lane & 15)) * STG_PITCH + (lane >> 4) * 16;
    if (kv) {
      proj_stage<true>(acc, 0, saddr, cs, st0.x, st0.y, st1.x, st1.y);
      proj_stage<false>(acc, 2, saddr, cs, st0.x, st0.y, st1.x, st1.y);
    } else if (type == 2) {
#pragma unroll
      for (int j = 0; j < 8; j += 2) proj_stage<false>(acc, j, saddr, cs, st0.x, st0.y, st1.x, st1.y);
    } else {
      const float sc = type == 0 ? QSCALE : 1.f, f0 = st0.y * sc, f1 = st1.y * sc;
#pragma unroll
      for (int j = 0; j < 8; j += 2) proj_stage<true>(acc, j, saddr, cs, st0.x, f0, st1.x, f1);
    }
    named_sync(wg + 1, 128);
    const int row = t & 63;
#pragma unroll
    for (int i = 0; i < 2; i++) {
      if (kv && i == 1) break;
      const int hh = 2 * i + (t >> 6);
      const uint32_t a = stg + row * STG_PITCH + hh * 32;
      const uint32_t ap = row >= 4 ? a - 4 * STG_PITCH : (r ? sbase + M_KTAIL + row * 128 + hh * 32 : 0u);
      proj_store(a, ap, kv ? 1 + hh : type, l + 1, kv ? 0 : ct * 4 + hh, row0 + row);
    }
    if (p == 1 && r == 0 && t < 32)
      *reinterpret_cast<uint4*>(sm + M_KTAIL + t * 16) = lds128(stg + (60 + (t >> 3)) * STG_PITCH + (t & 7) * 16);
  }
  __syncwarp();
  if (lane == 0) mbar_arrive(s_bar + B_EPI + p * 8);
}

__global__ void __launch_bounds__(640, 1) mega_kernel(const __grid_constant__ MegaParams P) {
  extern __shared__ __align__(1024) uint8_t sm[];
  constexpr uint32_t sbase = 1024;
  if (s2u(sm) != sbase) __trap();
  const uint32_t s_bar = sbase + M_BAR;
  const int tid = threadIdx.x, warp = tid >> 5, lane = tid & 31;
  TM(2, 0);
  if (tid == 0) {
    for (int i = 0; i < 4; i++) {
      mbar_init(s_bar + B_FULL + i * 8, 1); mbar_init(s_bar + B_EMPTY + i * 8, 4);
      mbar_init(s_bar + B_TURN + i * 8, 4); mbar_init(s_bar + B_EPI + i * 8, 4);
    }
    for (int i = 0; i < 2; i++) { mbar_init(s_bar + B_KV + i * 8, 1); mbar_init(s_bar + B_Q + i * 8, 1); mbar_init(s_bar + B_ODONE + i * 8, 16); }
    mbar_init(s_bar + B_FREE0, 16);
    mbar_init(s_bar + B_RES, 1);
    mbar_init(s_bar + B_PRE, 1);
    mbar_init(s_bar + B_CHK, 1);
    fence_bar_init();
  }
  if (tid < 512) *reinterpret_cast<uint4*>(sm + M_KV + 16 * 8192 + tid * 16) = make_uint4(0x3f803f80u, 0x3f803f80u, 0x3f803f80u, 0x3f803f80u);
  fence_async_smem();
  __syncthreads();
  const int wg = __shfl_sync(0xffffffffu, warp >> 2, 0);

  if (wg < 4) {
    asm volatile("setmaxnreg.inc.sync.aligned.u32 112;");
    pdl_wait();
    uint32_t pb = POLY_B;
    asm volatile("" : "+r"(pb));
    float s[32], o[12];
    uint32_t p0[16], p1[16];
#pragma unroll
    for (int i = 0; i < 32; i++) s[i] = ((MUFU_MASK >> (i >> 1)) & 1) ? 0.f : EXP_MAGIC;
#pragma unroll
    for (int i = 0; i < 12; i++) o[i] = 0.f;
    uint64_t dq = mkdesc(sbase + M_Q + wg * 2048, 128, 256, 0);
    uint64_t dk0 = mkdesc(sbase + M_KV + k_unit(0, 0) * 8192, 128, 256, 0), dk1 = mkdesc(sbase + M_KV + k_unit(0, 1) * 8192, 128, 256, 0);
    uint64_t dv = mkdesc(sbase + M_KV + v_unit(0, 0) * 8192, 128, 8192, 0);
    int pass_it = -1;
    mbar_wait_long(s_bar + B_Q, 0);
    mbar_wait_long(s_bar + B_KV, 0);
    TM1(3, 3);
    pin(o);
    att_step<false>(s, o, p1, p0, dq, dk0, dv, pb);
    {
#pragma unroll 1
      for (int it = 0; it < 32; it++) {
        const int b = it & 3;
        pin(o);
        att_step<true>(s, o, p0, p1, dq, dk0 + 128, dv, pb);
        att_step<true>(s, o, p1, p0, dq, dk0 + 256, dv + 64, pb);
        att_step<true>(s, o, p0, p1, dq, dk0 + 384, dv + 128, pb);
        att_step<true>(s, o, p1, p0, dq, dk1, dv + 192, pb);
        att_step<true>(s, o, p0, p1, dq, dk1 + 128, dv + 256, pb);
        att_step<true>(s, o, p1, p0, dq, dk1 + 256, dv + 320, pb);
        att_step<true>(s, o, p0, p1, dq, dk1 + 384, dv + 384, pb);
        wg_wait<0>();
        const uint64_t dvp = dv;
        dk0 -= 2048; dk1 -= 1024; dv += (1024ull << 32) - 2048ull;
        if (it == pass_it || b == 3) {
          const int lr = it >> 2, rnd = lr & 1, layer = lr >> 1, par = layer & 1;
          int t;
          asm volatile("mov.u32 %0, %%tid.x;" : "=r"(t));
          const int ln = t & 31, head = blockIdx.x >> 2;
          const int row0 = (blockIdx.x & 3) * 512 + rnd * 256 + wg * 64;
          pin(p1); pin(o);
          wg_fence();
          pv4(o, p1, dvp + 448);
          wg_commit();
          wg_wait<0>();
          pin(o); pin(s);
          if ((it & 7) == 5 && elect_one()) mbar_arrive(s_bar + B_FREE0);
          int code = (lr - 1) * 4 + ((wg - lr + 1) & 3);
          if (b == 3) {
            __nv_bfloat16* dst = g_o + (size_t)(row0 + ((t >> 5) & 3) * 16 + (ln >> 2)) * D_ + head * 16 + (ln & 3) * 2;
            const float l0 = o[8], l1 = o[10];
            float mx = 0.f;
#pragma unroll
            for (int i = 0; i < 8; i++) mx += fabsf(o[i]);
            const float i0 = __fdividef(1.f, l0), i1 = __fdividef(1.f, l1);
            *reinterpret_cast<uint32_t*>(dst) = pack_bf16(o[0] * i0, o[1] * i0);
            *reinterpret_cast<uint32_t*>(dst + 8) = pack_bf16(o[4] * i0, o[5] * i0);
            *reinterpret_cast<uint32_t*>(dst + 8 * D_) = pack_bf16(o[2] * i1, o[3] * i1);
            *reinterpret_cast<uint32_t*>(dst + 8 * D_ + 8) = pack_bf16(o[6] * i1, o[7] * i1);
            mbar_wait(s_bar + B_CHK, par);
            const bool ok = sm[M_CHK + par * 8 + rnd * 4 + wg] && l0 >= 1e-18f && l0 <= 1e37f &&
                            l1 >= 1e-18f && l1 <= 1e37f && mx <= 3e38f;
            uint32_t bad;
            asm volatile("{.reg .pred p, q; setp.eq.u32 p, %1, 0; barrier.red.or.pred.aligned q, %2, 128, p; selp.u32 %0, 1, 0, q;}"
                         : "=r"(bad) : "r"((uint32_t)ok), "r"(wg + 1) : "memory");
            if (bad) {
              att_fallback(P, layer, head, row0, reinterpret_cast<__nv_bfloat16*>(sm + M_Q + rnd * 8192 + wg * 2048), wg + 1);
              fence_async_smem();
            }
            __syncwarp();
            if (elect_one()) mbar_arrive(s_bar + B_ODONE + rnd * 8);
#pragma unroll
            for (int i = 0; i < 32; i++) s[i] = ((MUFU_MASK >> (i >> 1)) & 1) ? 0.f : EXP_MAGIC;
#pragma unroll
            for (int i = 0; i < 12; i++) o[i] = 0.f;
            const int pp = (wg - lr) & 3;
            code = pp == 0 ? lr * 4 : -1;
            pass_it = pp > 0 && pass_exists(lr, pp) ? it + ((rnd || pp == 1) ? 2 : 3) : -1;
            dq += rnd ? -512ll : 512ll;
            dk0 += 4 * 2048; dk1 += 4 * 1024; dv -= (4096ull << 32) - 4 * 2048ull;
          }
          if (code >= 0) {
            TM3(24 + code, 0);
            proj_pass(P, sm, sbase, code, wg);
            TM3(24 + code, 1);
          }
          if (it == 31) break;
          if (b & 1) {
            if (b == 3) mbar_wait_long(s_bar + B_Q + (~it & 4) * 2, ((it + 1) >> 3) & 1);
            mbar_wait_long(s_bar + B_KV + (~b & 2) * 4, ((it + 1) >> 3) & 1);
            if (b == 3) TM1(3 + ((it + 1) >> 2), 3);
          }
          pin(o);
          att_step<false>(s, o, p1, p0, dq, dk0, dv, pb);
        } else {
          if (b == 1) {
            TM1(3 + (it >> 2), 4);
            mbar_wait_long(s_bar + B_KV + 8, (it >> 3) & 1);
            TM1(3 + (it >> 2), 5);
          }
          att_step<true>(s, o, p1, p0, dq, dk0, dvp + 448, pb);
          wg_wait<0>();
          if ((it & 7) == 5 && elect_one()) mbar_arrive(s_bar + B_FREE0);
        }
      }
    }
  } else {
    asm volatile("setmaxnreg.dec.sync.aligned.u32 32;");
    const int w4 = __shfl_sync(0xffffffffu, warp & 3, 0);
    const int rb = blockIdx.x >> 3, ct = blockIdx.x & 7;
    if (EXP_NIT < 32 && EXP_AUX == 0) {
      if (w4 == 2) { pdl_wait(); load_q(sbase, 0, 0); load_kv(sbase, 0, 0); load_kv(sbase, 0, 1); load_q(sbase, 0, 1); }
    } else if (EXP_NIT < 32) {
      if (w4 == 2) { pdl_wait(); load_q(sbase, 0, 0); load_kv(sbase, 0, 0); load_kv(sbase, 0, 1); load_q(sbase, 0, 1); }
      mbar_wait_long(s_bar + B_ODONE + 8, 0);
    } else if (w4 == 0) {
      int code = 0;
      bool gated = true;
#pragma unroll 1
      while (code < 32) {
        code = __shfl_sync(0xffffffffu, code, 0);
        const int job = code >> 2, p = code & 3;
        const CUtensorMap* mb = b_map(P, code);
        const CUtensorMap* ma = &P.m[p == 0 ? 1 : 0];
        const int colb = b_col(code), rowa = tok0(job & 1, rb) + (p == 0 ? 0 : (code >> 3) * S_);
#pragma unroll 1
        for (int c = 0; c < 4; c++) {
          if (code > 0) mbar_wait(s_bar + B_EMPTY + c * 8, 1);
          if (elect_one()) {
            issue_b(sbase, mb, colb, c, c);
            if (!gated) issue_a(sbase, ma, rowa, c, c);
          }
        }
        if (gated) {
          if (p == 0) {
            if (code == 0) pdl_wait();
            else { const int prev = prev_pass(code); mbar_wait_long(s_bar + B_EPI + (prev & 3) * 8, (prev >> 2) & 1); }
            if (elect_one()) {
              asm volatile("fence.proxy.async;" ::: "memory");
              mbar_expect(s_bar + B_RES, 8192);
              tma_load(sbase + M_STG, &P.m[job < 2 ? 7 : 0], ct * 64, tok0(job & 1, rb) + (job < 2 ? 0 : ((job >> 1) - 1) * S_), s_bar + B_RES);
            }
            mbar_wait_long(s_bar + B_ODONE + (job & 1) * 8, (job >> 1) & 1);
            cnt_wait(CNT_O + job * 4 + (rb >> 2), 32);
            TM2(12 + job, 1);
          } else {
            mbar_wait_long(s_bar + B_EPI, job & 1);
            cnt_wait(CNT_X + job * 16 + rb, 8);
            TM2(12 + job, 3);
          }
          if (elect_one()) {
#pragma unroll
            for (int c = 0; c < 4; c++) issue_a(sbase, ma, rowa, c, c);
          }
        }
#pragma unroll 1
        for (int c = 0; c < 4; c++) {
          mbar_wait(s_bar + B_EMPTY + c * 8, 0);
          if (elect_one()) {
            issue_b(sbase, mb, colb, c, c + 4);
            issue_a(sbase, ma, rowa, c, c + 4);
          }
        }
        code = next_pass(code);
        gated = p == 0 || (code & 3) == 0;
      }
    } else if (w4 == 1) {
#pragma unroll 1
      for (int job = 0; job < 8; job++) {
        mbar_wait_long(s_bar + B_ODONE + (job & 1) * 8, (job >> 1) & 1);
        cnt_signal(CNT_O + job * 4 + (blockIdx.x & 3));
        if (job >= 6) continue;
        mbar_wait_long(s_bar + B_EPI, job & 1);
        cnt_signal(CNT_X + job * 16 + rb);
        if (pass_exists(job, 1)) {
          mbar_wait_long(s_bar + B_EPI + 8, job & 1);
          if (job & 2) mbar_wait_long(s_bar + B_EPI + 16, job & 1);
          cnt_signal(CNT_KV + job * 8 + ct);
        }
        mbar_wait_long(s_bar + B_EPI + 24, job & 1);
        cnt_signal(CNT_Q + (job * 4 + (rb >> 2)) * 8 + ct);
      }
    } else if (w4 == 2) {
      pdl_wait();
      load_q(sbase, 0, 0); load_kv(sbase, 0, 0); load_kv(sbase, 0, 1); load_q(sbase, 0, 1);
#pragma unroll 1
      for (int job = 0; job < 6; job++) {
        const int l = job >> 1, r = job & 1;
        mbar_wait_long(s_bar + B_ODONE + r * 8, l & 1);
        if (r == 0) mbar_wait_long(s_bar + B_FREE0, l & 1);
        mbar_wait_long(s_bar + B_TURN, job & 1);
        cnt_wait(CNT_KV + job * 8 + ((l & 1) ? blockIdx.x >> 4 : 0), 16);
        load_kv(sbase, l + 1, r);
        cnt_wait(CNT_Q + (job * 4 + (blockIdx.x & 3)) * 8 + (blockIdx.x >> 4), 4);
        load_q(sbase, l + 1, r);
      }
    } else {
      pdl_wait();
#pragma unroll 1
      for (int job = -1; job < 6; job++) {
        if (job & 1) {
          const int l = (job + 1) >> 1, head = blockIdx.x >> 2;
          if (job > 0) { mbar_wait_long(s_bar + B_KV + 8, l & 1); mbar_wait_long(s_bar + B_Q + 8, l & 1); }
          const float* nk = g_nrm + ((l * 2 + 1) * H_ + ((l & 1) ? 0 : head)) * 64;
          const unsigned q = __float_as_uint(__ldcg(g_nrm + (l * 2 * H_ + head) * 64 + (blockIdx.x & 3) * 16 + (lane & 15)));
          const unsigned kn = __reduce_max_sync(0xffffffffu, max(__float_as_uint(__ldcg(nk + lane)), __float_as_uint(__ldcg(nk + 32 + lane))));
          const unsigned qn = max(q, __shfl_xor_sync(0xffffffffu, q, 1));
          if (lane < 16 && !(lane & 1))
            sm[M_CHK + (l & 1) * 8 + (lane >> 1)] = __uint_as_float(qn) * __uint_as_float(kn) <= SCORE_LIMIT * SCORE_LIMIT;
          __syncwarp();
          if (elect_one()) mbar_arrive(s_bar + B_CHK);
        }
        if (job == 5) break;
        job++;
        float c[6];
#pragma unroll
        for (int i = 0; i < 6; i++) {
          const int p = 1 + (i >> 1);
          c[i] = __ldcg(g_colsum + ((job & 2) ? (p == 3 ? 0 : p * 512) + ct * 64 : (p == 3 ? 1536 + ct * 64 : 2048)) + (i & 1) * 32 + lane);
        }
        mbar_wait_long(s_bar + B_TURN, job & 1);
#pragma unroll
        for (int i = 0; i < 6; i++) reinterpret_cast<float*>(sm + M_CS)[i * 32 + lane] = c[i];
        __syncwarp();
        if (elect_one()) mbar_arrive(s_bar + B_PRE);
        job--;
      }
    }
    named_sync(5, 128);
    if (tid == 512) {
      unsigned old;
      asm volatile("atom.acq_rel.gpu.global.add.u32 %0, [%1], 1;" : "=r"(old) : "l"(g_cnt + CNT_DONE) : "memory");
      if (old == gridDim.x - 1)
        for (int i = 0; i < CNT_N; i++) g_cnt[i] = 0u;
    }
  }
}

typedef CUresult (*EncodeFn)(CUtensorMap*, CUtensorMapDataType, cuuint32_t, void*, const cuuint64_t*, const cuuint64_t*,
                             const cuuint32_t*, const cuuint32_t*, CUtensorMapInterleave, CUtensorMapSwizzle,
                             CUtensorMapL2promotion, CUtensorMapFloatOOBfill);

void make_map(EncodeFn enc, CUtensorMap* m, const void* p, int rows, int cols) {
  cuuint64_t dim[2] = {(cuuint64_t)cols, (cuuint64_t)rows};
  cuuint64_t str[1] = {(cuuint64_t)cols * 2};
  cuuint32_t box[2] = {64, 64};
  cuuint32_t es[2] = {1, 1};
  enc(m, CU_TENSOR_MAP_DATA_TYPE_BFLOAT16, 2, const_cast<void*>(p), dim, str, box, es, CU_TENSOR_MAP_INTERLEAVE_NONE,
      CU_TENSOR_MAP_SWIZZLE_128B, CU_TENSOR_MAP_L2_PROMOTION_L2_128B, CU_TENSOR_MAP_FLOAT_OOB_FILL_NONE);
}

template <typename... KA, typename... A>
void launch(void (*k)(KA...), int grid, int block, int smem, bool pdl, A... args) {
  cudaLaunchConfig_t cfg = {};
  cfg.gridDim = dim3(grid); cfg.blockDim = dim3(block); cfg.dynamicSmemBytes = smem; cfg.stream = cudaStreamPerThread;
  cudaLaunchAttribute at[1];
  at[0].id = cudaLaunchAttributeProgrammaticStreamSerialization;
  at[0].val.programmaticStreamSerializationAllowed = 1;
  cfg.attrs = at; cfg.numAttrs = pdl ? 1 : 0;
  cudaLaunchKernelEx(&cfg, k, KA(args)...);
}

struct HostState {
  bool init;
  const void* in[8];
  MegaParams mp;
};
HostState hs;

}

extern "C" void kernel_launch(void* const* d_in, const int* in_sizes, int n_in, void* d_out, int out_size) {
  const __nv_bfloat16* A_x = (const __nv_bfloat16*)d_in[0];
  const __nv_bfloat16* A_wqkv = (const __nv_bfloat16*)d_in[1];
  const __nv_bfloat16* A_wo = (const __nv_bfloat16*)d_in[2];
  const __nv_bfloat16* B_wq = (const __nv_bfloat16*)d_in[4];
  const __nv_bfloat16* B_wk = (const __nv_bfloat16*)d_in[5];
  const __nv_bfloat16* B_wv = (const __nv_bfloat16*)d_in[6];
  const __nv_bfloat16* B_wo = (const __nv_bfloat16*)d_in[7];
  bool same = hs.init;
  for (int i = 0; i < 8; i++) same = same && hs.in[i] == d_in[i];
  if (!same) {
    void* fn = nullptr;
    cudaDriverEntryPointQueryResult qr;
    cudaGetDriverEntryPoint("cuTensorMapEncodeTiled", &fn, cudaEnableDefault, &qr);
    EncodeFn enc = (EncodeFn)fn;
    void *px, *po, *pw;
    cudaGetSymbolAddress(&px, g_x);
    cudaGetSymbolAddress(&po, g_o);
    cudaGetSymbolAddress(&pw, g_wkv);
    make_map(enc, &hs.mp.m[7], A_x, S_, D_);
    make_map(enc, &hs.mp.m[0], px, 3 * S_, D_);
    make_map(enc, &hs.mp.m[1], po, S_, D_);
    make_map(enc, &hs.mp.m[2], A_wqkv, D_, 1536);
    make_map(enc, &hs.mp.m[3], B_wq, D_, 512);
    make_map(enc, &hs.mp.m[4], pw, D_, 32);
    make_map(enc, &hs.mp.m[5], A_wo, D_, D_);
    make_map(enc, &hs.mp.m[6], B_wo, D_, D_);
    hs.mp.x0 = A_x; hs.mp.wqkv = A_wqkv; hs.mp.wq = B_wq; hs.mp.wk = B_wk;
    cudaFuncSetAttribute(prep_kernel, cudaFuncAttributePreferredSharedMemoryCarveout, 100);
    cudaFuncSetAttribute(g1a_kernel, cudaFuncAttributeMaxDynamicSharedMemorySize, G1A_SMEM);
    cudaFuncSetAttribute(mega_kernel, cudaFuncAttributeMaxDynamicSharedMemorySize, MEGA_SMEM);
    for (int i = 0; i < 8; i++) hs.in[i] = d_in[i];
    hs.init = true;
  }
  hs.mp.out = (__nv_bfloat16*)d_out;
  launch(prep_kernel, 130, 256, 0, false, A_x, A_wqkv, B_wq, B_wk, B_wv);
  launch(g1a_kernel, 128, 288, G1A_SMEM, true, hs.mp.m[7], hs.mp.m[2]);
  launch(mega_kernel, 128, 640, MEGA_SMEM, true, hs.mp);
}
```

```cpp
#include <cuda_runtime.h>
#include <cuda_bf16.h>
#include <cuda_fp16.h>
#include <cuda.h>
#include <stdint.h>

namespace {

constexpr int S_ = 2048, D_ = 512, H_ = 32;

__device__ __align__(1024) __nv_bfloat16 g_x[3 * S_ * D_];
__device__ __align__(1024) __nv_bfloat16 g_o[S_ * D_];
__device__ __align__(1024) uint4 g_q[2 * H_ * S_ * 2];
__device__ __align__(1024) uint4 g_k[2 * H_ * S_ * 2];
__device__ __align__(1024) uint4 g_v[2 * H_ * S_ * 2];
__device__ __align__(1024) __nv_bfloat16 g_wkv[D_ * 32];
__device__ __align__(16) float2 g_stats[4 * S_ * 8];
__device__ __align__(16) float g_colsum[1536 + 512 + 64];
__device__ float g_nrm[4 * 2 * H_ * 64];
constexpr int CNT_O = 0, CNT_X = 128, CNT_KV = CNT_X + 128, CNT_Q = CNT_KV + 64, CNT_DONE = CNT_Q + 256, CNT_N = CNT_DONE + 1;
__device__ unsigned g_cnt[CNT_N];

#define EXP_NIT 32
#define EXP_AUX 0
#define TM(k, slot)
#define TM1(k, slot)
#define TM2(k, slot)
#define TM3(k, slot)
__device__ __forceinline__ uint32_t s2u(const void* p) { return (uint32_t)__cvta_generic_to_shared(p); }
__device__ __forceinline__ void mbar_init(uint32_t bar, int cnt) {
  asm volatile("mbarrier.init.shared::cta.b64 [%0], %1;" ::"r"(bar), "r"(cnt) : "memory");
}
__device__ __forceinline__ void mbar_expect(uint32_t bar, uint32_t bytes) {
  asm volatile("mbarrier.arrive.expect_tx.shared::cta.b64 _, [%0], %1;" ::"r"(bar), "r"(bytes) : "memory");
}
__device__ __forceinline__ void mbar_arrive(uint32_t bar) {
  asm volatile("mbarrier.arrive.shared::cta.b64 _, [%0];" ::"r"(bar) : "memory");
}
__device__ __forceinline__ void mbar_wait(uint32_t bar, uint32_t par) {
  uint32_t ok;
  int it = 0;
  do {
    asm volatile("{.reg .pred p; mbarrier.try_wait.parity.shared::cta.b64 p, [%1], %2; selp.u32 %0,1,0,p;}"
                 : "=r"(ok) : "r"(bar), "r"(par) : "memory");
    if (++it > (1 << 24)) __trap();
  } while (!ok);
}
#define SLEEP_NS 32
__device__ __forceinline__ void mbar_wait_long(uint32_t bar, uint32_t par) {
  uint32_t ok;
  int it = 0;
  while (true) {
    asm volatile("{.reg .pred p; mbarrier.test_wait.parity.shared::cta.b64 p, [%1], %2; selp.u32 %0,1,0,p;}"
                 : "=r"(ok) : "r"(bar), "r"(par) : "memory");
    if (ok) break;
    if (++it > (1 << 24)) __trap();
    __nanosleep(SLEEP_NS);
  }
}
__device__ __forceinline__ void bulk_load(uint32_t dst, const void* src, uint32_t bytes, uint32_t bar) {
  asm volatile("cp.async.bulk.shared::cluster.global.mbarrier::complete_tx::bytes [%0], [%1], %2, [%3];"
               ::"r"(dst), "l"(src), "r"(bytes), "r"(bar) : "memory");
}
__device__ __forceinline__ void tma_load(uint32_t dst, const CUtensorMap* m, int c0, int c1, uint32_t bar) {
  asm volatile("cp.async.bulk.tensor.2d.shared::cluster.global.mbarrier::complete_tx::bytes [%0], [%1, {%3, %4}], [%2];"
               ::"r"(dst), "l"(m), "r"(bar), "r"(c0), "r"(c1) : "memory");
}
__device__ __forceinline__ bool elect_one() {
  uint32_t p;
  asm volatile("{.reg .pred q; elect.sync _|q, 0xffffffff; selp.u32 %0, 1, 0, q;}" : "=r"(p));
  return p;
}
__device__ __forceinline__ void pdl_wait() { asm volatile("griddepcontrol.wait;" ::: "memory"); }
__device__ __forceinline__ void pdl_launch() { asm volatile("griddepcontrol.launch_dependents;" ::: "memory"); }
__device__ __forceinline__ void fence_async_smem() { asm volatile("fence.proxy.async.shared::cta;" ::: "memory"); }
__device__ __forceinline__ void fence_bar_init() { asm volatile("fence.mbarrier_init.release.cluster;" ::: "memory"); }
__device__ __forceinline__ void named_sync(int id, int n) { asm volatile("bar.sync %0, %1;" ::"r"(id), "r"(n) : "memory"); }
__device__ __forceinline__ void wg_fence() { asm volatile("wgmma.fence.sync.aligned;" ::: "memory"); }
__device__ __forceinline__ void wg_commit() { asm volatile("wgmma.commit_group.sync.aligned;" ::: "memory"); }
template <int N> __device__ __forceinline__ void wg_wait() { asm volatile("wgmma.wait_group.sync.aligned %0;" ::"n"(N) : "memory"); }
template <int N> __device__ __forceinline__ void pin(float (&d)[N]) {
#pragma unroll
  for (int i = 0; i < N; i++) asm volatile("" : "+f"(d[i])::"memory");
}
template <int N> __device__ __forceinline__ void pin(uint32_t (&d)[N]) {
#pragma unroll
  for (int i = 0; i < N; i++) asm volatile("" : "+r"(d[i])::"memory");
}
__device__ __forceinline__ uint64_t mkdesc(uint32_t addr, uint32_t lbo, uint32_t sbo, uint64_t swz) {
  return (uint64_t)((addr & 0x3FFFF) >> 4) | ((uint64_t)(lbo >> 4) << 16) | ((uint64_t)(sbo >> 4) << 32) | (swz << 62);
}
__device__ __forceinline__ uint32_t pack_bf16(float lo, float hi) {
  uint32_t d; asm("cvt.rn.bf16x2.f32 %0, %1, %2;" : "=r"(d) : "f"(hi), "f"(lo)); return d;
}
__device__ __forceinline__ uint32_t pack_f16(float lo, float hi) {
  uint32_t d; asm("cvt.rn.f16x2.f32 %0, %1, %2;" : "=r"(d) : "f"(hi), "f"(lo)); return d;
}
__device__ __forceinline__ float bf_lo(uint32_t v) { return __uint_as_float(v << 16); }
__device__ __forceinline__ float bf_hi(uint32_t v) { return __uint_as_float(v & 0xffff0000u); }
__device__ __forceinline__ void stsm4(uint32_t addr, uint32_t a, uint32_t b, uint32_t c, uint32_t d) {
  asm volatile("stmatrix.sync.aligned.m8n8.x4.shared.b16 [%0], {%1,%2,%3,%4};" ::"r"(addr), "r"(a), "r"(b), "r"(c), "r"(d) : "memory");
}
__device__ __forceinline__ void ldsm4(uint32_t addr, uint32_t& a, uint32_t& b, uint32_t& c, uint32_t& d) {
  asm volatile("ldmatrix.sync.aligned.m8n8.x4.shared.b16 {%0,%1,%2,%3}, [%4];" : "=r"(a), "=r"(b), "=r"(c), "=r"(d) : "r"(addr) : "memory");
}
__device__ __forceinline__ uint32_t hadd2_bf16(uint32_t a, uint32_t b) {
  uint32_t d; asm("add.rn.bf16x2 %0, %1, %2;" : "=r"(d) : "r"(a), "r"(b)); return d;
}
__device__ __forceinline__ uint4 lds128(uint32_t addr) {
  uint4 v; asm volatile("ld.shared.v4.u32 {%0,%1,%2,%3}, [%4];" : "=r"(v.x), "=r"(v.y), "=r"(v.z), "=r"(v.w) : "r"(addr) : "memory"); return v;
}

__device__ __forceinline__ void wgmma_qk_n64(float (&d)[32], uint64_t da, uint64_t db) {
  asm volatile("wgmma.mma_async.sync.aligned.m64n64k16.f32.f16.f16 "
      "{%0,%1,%2,%3,%4,%5,%6,%7,%8,%9,%10,%11,%12,%13,%14,%15,%16,%17,%18,%19,%20,%21,%22,%23,%24,%25,%26,%27,%28,%29,%30,%31}, "
      "%32, %33, 1, 1, 1, 0, 0;"
    : "+f"(d[0]), "+f"(d[1]), "+f"(d[2]), "+f"(d[3]), "+f"(d[4]), "+f"(d[5]), "+f"(d[6]), "+f"(d[7]), "+f"(d[8]),
      "+f"(d[9]), "+f"(d[10]), "+f"(d[11]), "+f"(d[12]), "+f"(d[13]), "+f"(d[14]), "+f"(d[15]), "+f"(d[16]),
      "+f"(d[17]), "+f"(d[18]), "+f"(d[19]), "+f"(d[20]), "+f"(d[21]), "+f"(d[22]), "+f"(d[23]), "+f"(d[24]),
      "+f"(d[25]), "+f"(d[26]), "+f"(d[27]), "+f"(d[28]), "+f"(d[29]), "+f"(d[30]), "+f"(d[31])
    : "l"(da), "l"(db));
}
__device__ __forceinline__ void wgmma_pv_n24(float (&d)[12], uint32_t a0, uint32_t a1, uint32_t a2, uint32_t a3, uint64_t db) {
  asm volatile("wgmma.mma_async.sync.aligned.m64n24k16.f32.bf16.bf16 "
      "{%0,%1,%2,%3,%4,%5,%6,%7,%8,%9,%10,%11}, "
      "{%12,%13,%14,%15}, %16, 1, 1, 1, 1;"
    : "+f"(d[0]), "+f"(d[1]), "+f"(d[2]), "+f"(d[3]), "+f"(d[4]), "+f"(d[5]), "+f"(d[6]), "+f"(d[7]), "+f"(d[8]),
      "+f"(d[9]), "+f"(d[10]), "+f"(d[11])
    : "r"(a0), "r"(a1), "r"(a2), "r"(a3), "l"(db));
}
__device__ __forceinline__ void wgmma_gemm_n64(float (&d)[32], uint64_t da, uint64_t db) {
  asm volatile("wgmma.mma_async.sync.aligned.m64n64k16.f32.bf16.bf16 "
      "{%0,%1,%2,%3,%4,%5,%6,%7,%8,%9,%10,%11,%12,%13,%14,%15,%16,%17,%18,%19,%20,%21,%22,%23,%24,%25,%26,%27,%28,%29,%30,%31}, "
      "%32, %33, 1, 1, 1, 0, 1;"
    : "+f"(d[0]), "+f"(d[1]), "+f"(d[2]), "+f"(d[3]), "+f"(d[4]), "+f"(d[5]), "+f"(d[6]), "+f"(d[7]), "+f"(d[8]),
      "+f"(d[9]), "+f"(d[10]), "+f"(d[11]), "+f"(d[12]), "+f"(d[13]), "+f"(d[14]), "+f"(d[15]), "+f"(d[16]),
      "+f"(d[17]), "+f"(d[18]), "+f"(d[19]), "+f"(d[20]), "+f"(d[21]), "+f"(d[22]), "+f"(d[23]), "+f"(d[24]),
      "+f"(d[25]), "+f"(d[26]), "+f"(d[27]), "+f"(d[28]), "+f"(d[29]), "+f"(d[30]), "+f"(d[31])
    : "l"(da), "l"(db));
}
__device__ __forceinline__ void wgmma_gemm_n32(float (&d)[16], uint64_t da, uint64_t db) {
  asm volatile("wgmma.mma_async.sync.aligned.m64n32k16.f32.bf16.bf16 "
      "{%0,%1,%2,%3,%4,%5,%6,%7,%8,%9,%10,%11,%12,%13,%14,%15}, "
      "%16, %17, 1, 1, 1, 0, 1;"
    : "+f"(d[0]), "+f"(d[1]), "+f"(d[2]), "+f"(d[3]), "+f"(d[4]), "+f"(d[5]), "+f"(d[6]), "+f"(d[7]), "+f"(d[8]),
      "+f"(d[9]), "+f"(d[10]), "+f"(d[11]), "+f"(d[12]), "+f"(d[13]), "+f"(d[14]), "+f"(d[15])
    : "l"(da), "l"(db));
}
__device__ __forceinline__ void wgmma_gemm_n192(float (&d)[96], uint64_t da, uint64_t db) {
  asm volatile("wgmma.mma_async.sync.aligned.m64n192k16.f32.bf16.bf16 "
      "{%0,%1,%2,%3,%4,%5,%6,%7,%8,%9,%10,%11,%12,%13,%14,%15,%16,%17,%18,%19,%20,%21,%22,%23,%24,%25,%26,%27,%28,%29,%30,%31,%32,%33,%34,%35,%36,%37,%38,%39,%40,%41,%42,%43,%44,%45,%46,%47,%48,%49,%50,%51,%52,%53,%54,%55,%56,%57,%58,%59,%60,%61,%62,%63,%64,%65,%66,%67,%68,%69,%70,%71,%72,%73,%74,%75,%76,%77,%78,%79,%80,%81,%82,%83,%84,%85,%86,%87,%88,%89,%90,%91,%92,%93,%94,%95}, "
      "%96, %97, 1, 1, 1, 0, 1;"
    : "+f"(d[0]), "+f"(d[1]), "+f"(d[2]), "+f"(d[3]), "+f"(d[4]), "+f"(d[5]), "+f"(d[6]), "+f"(d[7]), "+f"(d[8]),
      "+f"(d[9]), "+f"(d[10]), "+f"(d[11]), "+f"(d[12]), "+f"(d[13]), "+f"(d[14]), "+f"(d[15]), "+f"(d[16]),
      "+f"(d[17]), "+f"(d[18]), "+f"(d[19]), "+f"(d[20]), "+f"(d[21]), "+f"(d[22]), "+f"(d[23]), "+f"(d[24]),
      "+f"(d[25]), "+f"(d[26]), "+f"(d[27]), "+f"(d[28]), "+f"(d[29]), "+f"(d[30]), "+f"(d[31]), "+f"(d[32]),
      "+f"(d[33]), "+f"(d[34]), "+f"(d[35]), "+f"(d[36]), "+f"(d[37]), "+f"(d[38]), "+f"(d[39]), "+f"(d[40]),
      "+f"(d[41]), "+f"(d[42]), "+f"(d[43]), "+f"(d[44]), "+f"(d[45]), "+f"(d[46]), "+f"(d[47]), "+f"(d[48]),
      "+f"(d[49]), "+f"(d[50]), "+f"(d[51]), "+f"(d[52]), "+f"(d[53]), "+f"(d[54]), "+f"(d[55]), "+f"(d[56]),
      "+f"(d[57]), "+f"(d[58]), "+f"(d[59]), "+f"(d[60]), "+f"(d[61]), "+f"(d[62]), "+f"(d[63]), "+f"(d[64]),
      "+f"(d[65]), "+f"(d[66]), "+f"(d[67]), "+f"(d[68]), "+f"(d[69]), "+f"(d[70]), "+f"(d[71]), "+f"(d[72]),
      "+f"(d[73]), "+f"(d[74]), "+f"(d[75]), "+f"(d[76]), "+f"(d[77]), "+f"(d[78]), "+f"(d[79]), "+f"(d[80]),
      "+f"(d[81]), "+f"(d[82]), "+f"(d[83]), "+f"(d[84]), "+f"(d[85]), "+f"(d[86]), "+f"(d[87]), "+f"(d[88]),
      "+f"(d[89]), "+f"(d[90]), "+f"(d[91]), "+f"(d[92]), "+f"(d[93]), "+f"(d[94]), "+f"(d[95])
    : "l"(da), "l"(db));
}

constexpr float QSCALE = 0.25f * 1.4426950408889634f;
constexpr float LN_EPS = 1e-5f;

__device__ __forceinline__ void row_stats(int layer, int row, float& mu, float& rstd) {
  const float4* p = reinterpret_cast<const float4*>(g_stats + (layer * S_ + row) * 8);
  float4 a = __ldcg(p), b = __ldcg(p + 1), c = __ldcg(p + 2), d = __ldcg(p + 3);
  float s = (a.x + a.z) + (b.x + b.z) + (c.x + c.z) + (d.x + d.z);
  float q = (a.y + a.w) + (b.y + b.w) + (c.y + c.w) + (d.y + d.w);
  mu = s * (1.f / D_);
  float var = fmaxf(q * (1.f / D_) - mu * mu, 0.f);
  rstd = rsqrtf(var + LN_EPS);
}

__global__ void __launch_bounds__(256) prep_kernel(const __nv_bfloat16* __restrict__ x, const __nv_bfloat16* __restrict__ wqkv,
                                                   const __nv_bfloat16* __restrict__ wq, const __nv_bfloat16* __restrict__ wk,
                                                   const __nv_bfloat16* __restrict__ wv) {
  TM(0, 0);
  pdl_launch();
  __shared__ float red[8][16];
  const int b = blockIdx.x, tid = threadIdx.x, lane = tid & 31, warp = tid >> 5;
  {
    const __nv_bfloat16* w; int ld, out;
    if (b < 96) { w = wqkv + b * 16; ld = 1536; out = b * 16; }
    else if (b < 128) { w = wq + (b - 96) * 16; ld = 512; out = 1536 + (b - 96) * 16; }
    else { w = (b == 128) ? wk : wv; ld = 16; out = 2048 + (b - 128) * 16; }
    const int half = tid & 1, r0 = tid >> 1;
    float acc[8];
#pragma unroll
    for (int i = 0; i < 8; i++) acc[i] = 0.f;
#pragma unroll
    for (int j = 0; j < 4; j++) {
      uint4 v = __ldg(reinterpret_cast<const uint4*>(w + (size_t)(r0 + 128 * j) * ld + half * 8));
      if (b >= 128) *reinterpret_cast<uint4*>(g_wkv + (r0 + 128 * j) * 32 + (b - 128) * 16 + half * 8) = v;
      acc[0] += bf_lo(v.x); acc[1] += bf_hi(v.x); acc[2] += bf_lo(v.y); acc[3] += bf_hi(v.y);
      acc[4] += bf_lo(v.z); acc[5] += bf_hi(v.z); acc[6] += bf_lo(v.w); acc[7] += bf_hi(v.w);
    }
#pragma unroll
    for (int i = 0; i < 8; i++) {
#pragma unroll
      for (int o = 2; o < 32; o <<= 1) acc[i] += __shfl_xor_sync(0xffffffffu, acc[i], o);
    }
    if (lane < 2) {
#pragma unroll
      for (int i = 0; i < 8; i++) red[warp][lane * 8 + i] = acc[i];
    }
    __syncthreads();
    if (tid < 16) {
      float s = 0.f;
#pragma unroll
      for (int w8 = 0; w8 < 8; w8++) s += red[w8][tid];
      g_colsum[out + tid] = s;
    }
    if (b == 129 && tid >= 32 && tid < 64) g_colsum[2048 + tid] = 0.f;
  }
  if (b < 128) {
#pragma unroll
    for (int j = 0; j < 2; j++) {
      const int row = b * 16 + warp * 2 + j;
      const uint4* p = reinterpret_cast<const uint4*>(x + (size_t)row * D_ + lane * 16);
      uint4 v0 = __ldg(p), v1 = __ldg(p + 1);
      uint32_t u[8] = {v0.x, v0.y, v0.z, v0.w, v1.x, v1.y, v1.z, v1.w};
      float s = 0.f, q = 0.f;
#pragma unroll
      for (int i = 0; i < 8; i++) {
        float a = bf_lo(u[i]), c = bf_hi(u[i]);
        s += a + c; q = fmaf(a, a, fmaf(c, c, q));
      }
      s += __shfl_xor_sync(0xffffffffu, s, 1); q += __shfl_xor_sync(0xffffffffu, q, 1);
      s += __shfl_xor_sync(0xffffffffu, s, 2); q += __shfl_xor_sync(0xffffffffu, q, 2);
      if ((lane & 3) == 0) g_stats[row * 8 + (lane >> 2)] = make_float2(s, q);
    }
  }
  TM(0, 4);
}

__device__ __forceinline__ int tok0(int r, int rb) { return (rb >> 2) * 512 + r * 256 + (rb & 3) * 64; }
__device__ __forceinline__ int key_pos(int token) {
  const int r = (token >> 8) & 1, rb = ((token >> 9) << 2) | ((token >> 6) & 3), row = token & 63;
  return (16 * r + (row >> 2)) * 64 + rb * 4 + (row & 3);
}
__device__ __forceinline__ float sq_norm16(const uint4& a, const uint4& b) {
  const uint32_t u[8] = {a.x, a.y, a.z, a.w, b.x, b.y, b.z, b.w};
  __half2 n = __hmul2(*reinterpret_cast<const __half2*>(&u[0]), *reinterpret_cast<const __half2*>(&u[0]));
#pragma unroll
  for (int i = 1; i < 8; i++) n = __hfma2(*reinterpret_cast<const __half2*>(&u[i]), *reinterpret_cast<const __half2*>(&u[i]), n);
  return __low2float(n) + __high2float(n);
}
__device__ __forceinline__ uint32_t hsub2(uint32_t a, uint32_t b) {
  uint32_t d; asm("sub.rn.f16x2 %0, %1, %2;" : "=r"(d) : "r"(a), "r"(b)); return d;
}
__device__ __forceinline__ void proj_store(uint32_t a, uint32_t ap, int type, int layer, int head, int token) {
  const uint4 v0 = lds128(a), v1 = lds128(a + 16);
  const size_t hb = (size_t)((layer & 1) * H_ + head) * (S_ * 2);
  if (type == 2) {
    uint4* dst = g_v + hb + key_pos(token);
    dst[0] = v0; dst[S_] = v1;
    return;
  }
  if (type == 0) {
    uint4* dst = g_q + hb + (token >> 3) * 16 + (token & 7);
    dst[0] = v0; dst[8] = v1;
  } else {
    uint4 d0 = v0, d1 = v1;
    if (ap) {
      const uint4 p0 = lds128(ap), p1 = lds128(ap + 16);
      d0 = make_uint4(hsub2(v0.x, p0.x), hsub2(v0.y, p0.y), hsub2(v0.z, p0.z), hsub2(v0.w, p0.w));
      d1 = make_uint4(hsub2(v1.x, p1.x), hsub2(v1.y, p1.y), hsub2(v1.z, p1.z), hsub2(v1.w, p1.w));
    }
    const int pos = key_pos(token);
    uint4* dst = g_k + hb + (pos >> 3) * 16 + (pos & 7);
    dst[0] = d0; dst[8] = d1;
  }
  const unsigned m = __reduce_max_sync(0xffffffffu, __float_as_uint(sq_norm16(v0, v1)) & 0x7fffffffu);
  if ((threadIdx.x & 31) == 0) g_nrm[((layer * 2 + type) * H_ + head) * 64 + (token >> 5)] = __uint_as_float(m);
}
template <bool F16, int N>
__device__ __forceinline__ void proj_stage(const float (&acc)[N], int j  , uint32_t addr, const float* cs,
                                           float mu0, float f0, float mu1, float f1) {
  uint32_t r[4];
#pragma unroll
  for (int e = 0; e < 2; e++) {
    const float2 c = *reinterpret_cast<const float2*>(cs + (j + e) * 8);
    const float a0 = fmaf(-mu0, c.x, acc[(j + e) * 4 + 0]) * f0, a1 = fmaf(-mu0, c.y, acc[(j + e) * 4 + 1]) * f0;
    const float a2 = fmaf(-mu1, c.x, acc[(j + e) * 4 + 2]) * f1, a3 = fmaf(-mu1, c.y, acc[(j + e) * 4 + 3]) * f1;
    r[e * 2] = F16 ? pack_f16(a0, a1) : pack_bf16(a0, a1);
    r[e * 2 + 1] = F16 ? pack_f16(a2, a3) : pack_bf16(a2, a3);
  }
  stsm4(addr + j * 16, r[0], r[1], r[2], r[3]);
}

constexpr int G1A_NS = 5, G1A_STAGE = 16384 + 3 * 8192, G1A_PITCH = 400;
constexpr int G1A_SMEM = G1A_NS * G1A_STAGE + 1024 + 192 * 4 + 128;
__global__ void __launch_bounds__(288, 1) g1a_kernel(const __grid_constant__ CUtensorMap mx, const __grid_constant__ CUtensorMap mw) {
  extern __shared__ uint8_t smem_raw[];
  const uint32_t sbase = (s2u(smem_raw) + 1023) & ~1023u;
  const uint32_t s_cs = sbase + G1A_NS * G1A_STAGE, s_bar = s_cs + 192 * 4;
  float* cs = reinterpret_cast<float*>(smem_raw + (s_cs - s2u(smem_raw)));
  const int tid = threadIdx.x, warp = tid >> 5, lane = tid & 31;
  const int nb = blockIdx.x & 7, rb = blockIdx.x >> 3;
  TM(1, 0);
  if (tid == 0) {
    for (int i = 0; i < G1A_NS; i++) { mbar_init(s_bar + i * 8, 1); mbar_init(s_bar + 40 + i * 8, 2); }
    fence_bar_init();
  }
  __syncthreads();
  if (warp == 8) {
    if (lane == 0) {
      for (int c = 0; c < 8; c++) {
        const int s = c < G1A_NS ? c : c - G1A_NS;
        const uint32_t st = sbase + s * G1A_STAGE, bar = s_bar + s * 8;
        if (c >= G1A_NS) mbar_wait(s_bar + 40 + s * 8, 0);
        mbar_expect(bar, G1A_STAGE);
        tma_load(st, &mx, c * 64, tok0(0, rb), bar);
        tma_load(st + 8192, &mx, c * 64, tok0(1, rb), bar);
        for (int j = 0; j < 3; j++) tma_load(st + 16384 + j * 8192, &mw, nb * 192 + j * 64, c * 64, bar);
      }
    }
    return;
  }
  const int wg = warp >> 2;
  float acc[96];
#pragma unroll
  for (int i = 0; i < 96; i++) acc[i] = 0.f;
  pin(acc);
#pragma unroll 1
  for (int c = 0; c < 8; c++) {
    const int s = c < G1A_NS ? c : c - G1A_NS;
    mbar_wait(s_bar + s * 8, c >= G1A_NS);
    if (c == 0) TM(1, 2);
    const uint32_t st = sbase + s * G1A_STAGE;
    const uint64_t da = mkdesc(st + wg * 8192, 16, 1024, 1), db = mkdesc(st + 16384, 8192, 1024, 1);
    wg_fence();
#pragma unroll
    for (int k = 0; k < 4; k++) wgmma_gemm_n192(acc, da + k * 2, db + k * 128);
    wg_commit();
    if (c >= 1 && c <= 3) { wg_wait<1>(); if ((tid & 127) == 0) mbar_arrive(s_bar + 40 + (c - 1) * 8); }
    if (c == 5) {
      pdl_wait();
      pdl_launch();
      if (tid < 192) cs[tid] = __ldcg(g_colsum + nb * 192 + tid);
    }
  }
  float mu0, rs0, mu1, rs1;
  const int row0 = tok0(wg, rb) + (warp & 3) * 16 + (lane >> 2);
  row_stats(0, row0, mu0, rs0); row_stats(0, row0 + 8, mu1, rs1);
  wg_wait<0>();
  pin(acc);
  TM(1, 3);
  named_sync(1, 256);
  {
    const uint32_t addr = sbase + (wg * 64 + (warp & 3) * 16 + (lane & 15)) * G1A_PITCH + (lane >> 4) * 16;
#pragma unroll
    for (int j = 0; j < 24; j += 2) {
      const int type = (nb * 12 + (j >> 1)) >> 5;
      const float sc = type == 0 ? QSCALE : 1.f;
      if (type == 2) proj_stage<false>(acc, j, addr, cs + (lane & 3) * 2, mu0, rs0, mu1, rs1);
      else proj_stage<true>(acc, j, addr, cs + (lane & 3) * 2, mu0, rs0 * sc, mu1, rs1 * sc);
    }
  }
  named_sync(1, 256);
#pragma unroll
  for (int it = 0; it < 6; it++) {
    const int item = warp + it * 8, hh = item >> 2, trow = (item & 3) * 32 + lane;
    const int hg = nb * 12 + hh;
    const uint32_t a = sbase + trow * G1A_PITCH + hh * 32;
    proj_store(a, trow >= 4 ? a - 4 * G1A_PITCH : 0u, hg >> 5, 0, hg & 31, tok0(trow >> 6, rb) + (trow & 63));
  }
  TM(1, 4);
}

constexpr uint32_t MUFU_MASK = 0xF800u;
constexpr float EXP_MAGIC = 383.0f + 0.65f / 128.0f;
constexpr uint32_t POLY_A = 0x5a835a83u, POLY_B = 0x92a192a1u, POLY_C = 0x800b800bu;
constexpr float SCORE_LIMIT = 116.f;

__device__ __forceinline__ void exp_step(const float (&s)[32], uint32_t (&p)[16], uint32_t pb) {
#pragma unroll
  for (int i = 0; i < 16; i++) {
    if ((MUFU_MASK >> i) & 1) {
      float a, b;
      asm("ex2.approx.ftz.f32 %0, %1;" : "=f"(a) : "f"(s[2 * i]));
      asm("ex2.approx.ftz.f32 %0, %1;" : "=f"(b) : "f"(s[2 * i + 1]));
      p[i] = pack_bf16(a, b);
    } else {
      uint32_t z, u, h;
      asm("prmt.b32 %0, %1, %2, 0x6521;" : "=r"(z) : "r"(__float_as_uint(s[2 * i])), "r"(__float_as_uint(s[2 * i + 1])));
      asm("fma.rn.f16x2 %0, %1, %2, %3;" : "=r"(u) : "r"(z & 0x007f007fu), "r"(POLY_A), "r"(pb));
      asm("fma.rn.f16x2 %0, %1, %1, %2;" : "=r"(h) : "r"(u), "r"(POLY_C));
      p[i] = z - h;
    }
  }
}

__device__ __forceinline__ void pv4(float (&o)[12], const uint32_t (&p)[16], uint64_t dv) {
#pragma unroll
  for (int j = 0; j < 4; j++) wgmma_pv_n24(o, p[4 * j], p[4 * j + 1], p[4 * j + 2], p[4 * j + 3], dv + j * 16);
}
template <bool PV>
__device__ __forceinline__ void att_step(float (&s)[32], float (&o)[12], uint32_t (&pin_)[16], uint32_t (&pout)[16], uint64_t dq,
                                         uint64_t dk, uint64_t dv, uint32_t pb) {
  pin(s);
  if (PV) pin(pin_);
  wg_fence();
  wgmma_qk_n64(s, dq, dk);
  wg_commit();
  if (PV) {
#pragma unroll
    for (int j = 0; j < 4; j++) wgmma_pv_n24(o, pin_[4 * j], pin_[4 * j + 1], pin_[4 * j + 2], pin_[4 * j + 3], dv + j * 16);
    wg_commit();
    wg_wait<1>();
  } else {
    wg_wait<0>();
  }
  pin(s);
  exp_step(s, pout, pb);
  pin(pout);
}

constexpr int M_STAGE = 0;
constexpr int M_STG = 65536, STG_PITCH = 144;
constexpr int M_KV = 74752;
constexpr int M_Q = M_KV + 17 * 8192;
constexpr int M_CS = M_Q + 16384, M_KTAIL = M_CS + 768, M_ROW = M_KTAIL + 512, M_BAR = M_ROW + 512;
constexpr int MEGA_SMEM = M_BAR + 256;
__device__ __forceinline__ int k_unit(int b, int j) { return j == 0 ? 12 - 4 * b : 7 - 2 * b; }
__device__ __forceinline__ int v_unit(int b, int j) { return j == 0 ? 14 - 4 * b : 15 - 2 * b; }
constexpr int B_FULL = 0, B_EMPTY = 32, B_KV = 64, B_Q = 80, B_FREE0 = 96, B_ODONE = 104, B_RES = 120, B_PRE = 128,
              B_TURN = 136, B_EPI = 168, B_CHK = 200, M_CHK = M_BAR + 208;

struct MegaParams {
  CUtensorMap m[8];
  const __nv_bfloat16* x0;
  const __nv_bfloat16* wqkv; const __nv_bfloat16* wq; const __nv_bfloat16* wk;
  __nv_bfloat16* out;
};

__device__ __forceinline__ void cnt_signal(int idx, unsigned n = 1) {
  if (elect_one()) asm volatile("red.release.gpu.global.add.u32 [%0], %1;" ::"l"(g_cnt + idx), "r"(n) : "memory");
}
__device__ __forceinline__ void cnt_wait(int idx, unsigned target) {
  unsigned v;
  int it = 0;
  while (true) {
    asm volatile("ld.acquire.gpu.global.u32 %0, [%1];" : "=r"(v) : "l"(g_cnt + idx) : "memory");
    if (v >= target) break;
    if (++it > (1 << 24)) __trap();
  }
  asm volatile("fence.proxy.async.global;" ::: "memory");
}

__device__ __forceinline__ void att_fallback(const MegaParams& P, int layer, int head, int row0, __nv_bfloat16* sk, int bar_id) {
  int t;
  asm volatile("mov.u32 %0, %%tid.x;" : "=r"(t));
  t &= 127;
  const int hf = t & 1;
  asm volatile("" : "+r"(layer), "+r"(head), "+r"(row0));
  const __nv_bfloat16* x = layer == 0 ? P.x0 : g_x + (size_t)(layer - 1) * S_ * D_;
  const bool mqa = layer & 1;
  const __nv_bfloat16* vimg = reinterpret_cast<const __nv_bfloat16*>(g_v + (size_t)((layer & 1) * H_ + (mqa ? 0 : head)) * (S_ * 2));
  float q[16], o[16], acc[16];
  float m = -INFINITY, l = 0.f;
#pragma unroll
  for (int d = 0; d < 16; d++) { o[d] = 0.f; q[d] = 0.f; }
#pragma unroll 1
  for (int ch = -1; ch < 32; ch++) {
    const int token = ch < 0 ? row0 + (t >> 1) : ch * 64 + (t >> 1);
    const __nv_bfloat16* w = ch < 0 ? (mqa ? P.wq : P.wqkv) + head * 16 : (mqa ? P.wk : P.wqkv + 512 + head * 16);
    const int ld = mqa ? (ch < 0 ? 512 : 16) : 1536;
    float mu, rs;
    row_stats(layer, token, mu, rs);
#pragma unroll
    for (int d = 0; d < 16; d++) acc[d] = 0.f;
#pragma unroll 1
    for (int k = hf * 256; k < hf * 256 + 256; k++) {
      const unsigned short xr = __ldcg(reinterpret_cast<const unsigned short*>(x) + (size_t)token * D_ + k);
      const float xn = __bfloat162float(__float2bfloat16((__uint_as_float((uint32_t)xr << 16) - mu) * rs));
#pragma unroll
      for (int d = 0; d < 16; d++) acc[d] = fmaf(xn, __bfloat162float(w[(size_t)k * ld + d]), acc[d]);
    }
#pragma unroll
    for (int d = 0; d < 16; d++) acc[d] = __bfloat162float(__float2bfloat16(acc[d] + __shfl_xor_sync(0xffffffffu, acc[d], 1)));
    if (ch < 0) {
#pragma unroll
      for (int d = 0; d < 16; d++) q[d] = acc[d];
      continue;
    }
    named_sync(bar_id, 128);
    if (hf == 0) {
#pragma unroll
      for (int d = 0; d < 16; d++) sk[(t >> 1) * 16 + d] = __float2bfloat16(acc[d]);
    }
    named_sync(bar_id, 128);
#pragma unroll 1
    for (int j = hf * 32; j < hf * 32 + 32; j++) {
      float sc = 0.f;
#pragma unroll
      for (int d = 0; d < 16; d++) sc = fmaf(q[d], __bfloat162float(sk[j * 16 + d]), sc);
      sc *= 0.25f;
      if (sc > m || sc != sc) {
        const float a = __expf(m - sc);
        l *= a;
#pragma unroll
        for (int d = 0; d < 16; d++) o[d] *= a;
        m = sc;
      }
      const float p = __expf(sc - m);
      l += p;
      const int pos = key_pos(ch * 64 + j);
#pragma unroll
      for (int d = 0; d < 16; d++) {
        const unsigned short vr = __ldcg(reinterpret_cast<const unsigned short*>(vimg) + (d >> 3) * (S_ * 8) + pos * 8 + (d & 7));
        o[d] = fmaf(p, __uint_as_float((uint32_t)vr << 16), o[d]);
      }
    }
  }
  const float m2 = __shfl_xor_sync(0xffffffffu, m, 1), mm = fmaxf(m, m2), a = __expf(m - mm);
  l *= a; l += __shfl_xor_sync(0xffffffffu, l, 1);
  const float inv = 1.f / l;
  __nv_bfloat16* dst = g_o + (size_t)(row0 + (t >> 1)) * D_ + head * 16;
#pragma unroll
  for (int d = 0; d < 16; d++) {
    float v = o[d] * a; v += __shfl_xor_sync(0xffffffffu, v, 1);
    if ((d >> 3) == hf) dst[d] = __float2bfloat16(v * inv);
  }
}

__device__ __forceinline__ const CUtensorMap* b_map(const MegaParams& P, int code) {
  const int l = code >> 3, p = code & 3;
  return &P.m[p == 0 ? 5 + (l & 1) : ((l & 1) ? 2 : (p == 3 ? 3 : 4))];
}
__device__ __forceinline__ int b_col(int code) {
  const int p = code & 3, ct = blockIdx.x & 7;
  return p == 0 || p == 3 ? ct * 64 : ((code & 8) ? p * 512 + ct * 64 : 0);
}
__device__ __forceinline__ void issue_b(uint32_t sbase, const CUtensorMap* m, int col, int st, int c) {
  mbar_expect(sbase + M_BAR + B_FULL + st * 8, 16384);
  tma_load(sbase + M_STAGE + st * 16384 + 8192, m, col, c * 64, sbase + M_BAR + B_FULL + st * 8);
}
__device__ __forceinline__ void issue_a(uint32_t sbase, const CUtensorMap* m, int row, int st, int c) {
  tma_load(sbase + M_STAGE + st * 16384, m, c * 64, row, sbase + M_BAR + B_FULL + st * 8);
}
__device__ __forceinline__ void load_kv(uint32_t sbase, int l, int r) {
  const size_t hb = (size_t)((l & 1) * H_ + ((l & 1) ? 0 : blockIdx.x >> 2)) * 65536;
  const uint8_t* gk = reinterpret_cast<const uint8_t*>(g_k) + hb;
  const uint8_t* gv = reinterpret_cast<const uint8_t*>(g_v) + hb;
  const uint32_t bar = sbase + M_BAR + B_KV + r * 8;
  if (elect_one()) {
    mbar_expect(bar, 65536);
#pragma unroll
    for (int j = 0; j < 2; j++) {
      const int b = r * 2 + j;
      bulk_load(sbase + M_KV + k_unit(b, 0) * 8192, gk + b * 16384, 8192, bar);
      bulk_load(sbase + M_KV + v_unit(b, 0) * 8192, gv + b * 8192, 8192, bar);
      bulk_load(sbase + M_KV + v_unit(b, 1) * 8192, gv + 32768 + b * 8192, 8192, bar);
      bulk_load(sbase + M_KV + k_unit(b, 1) * 8192, gk + b * 16384 + 8192, 8192, bar);
    }
  }
}
__device__ __forceinline__ void load_q(uint32_t sbase, int l, int r) {
  const uint32_t bar = sbase + M_BAR + B_Q + r * 8;
  if (elect_one()) {
    mbar_expect(bar, 8192);
    bulk_load(sbase + M_Q + r * 8192,
              reinterpret_cast<const uint8_t*>(g_q) + (size_t)((l & 1) * H_ + (blockIdx.x >> 2)) * 65536 + (blockIdx.x & 3) * 16384 + r * 8192,
              8192, bar);
  }
}

__device__ __forceinline__ bool pass_exists(int job, int p) {
  return p == 0 || (job < 6 && (p == 3 || (job & 2) || (p == 1 && (blockIdx.x & 7) == 0)));
}
__device__ __forceinline__ int next_pass(int code) {
  const int job = code >> 2, p = code & 3;
  if (p == 0 && pass_exists(job, 1)) return code + 1;
  if (p == 1 && pass_exists(job, 2)) return code + 1;
  if (p < 3 && pass_exists(job, 3)) return job * 4 + 3;
  return job * 4 + 4;
}
__device__ __forceinline__ int prev_pass(int code) {
  const int job = code >> 2, p = code & 3;
  if (p == 0) return job > 6 ? (job - 1) * 4 : (job - 1) * 4 + 3;
  if (p == 3 && pass_exists(job, 2)) return code - 1;
  if (p >= 2 && pass_exists(job, 1)) return job * 4 + 1;
  return job * 4;
}

__device__ __forceinline__ void proj_pass(const MegaParams& P, uint8_t* sm, uint32_t sbase, int code, int wg) {
  const uint32_t s_bar = sbase + M_BAR;
  const int prev = prev_pass(code);
  if (code > 0) mbar_wait_long(s_bar + B_TURN + (prev & 3) * 8, (prev >> 2) & 1);
  float acc[32];
#pragma unroll
  for (int i = 0; i < 32; i++) acc[i] = 0.f;
  pin(acc);
#pragma unroll
  for (int c = 0; c < 8; c++) {
    const uint32_t st = sbase + M_STAGE + (c & 3) * 16384;
    mbar_wait(s_bar + B_FULL + (c & 3) * 8, c >> 2);
    const uint64_t da = mkdesc(st, 16, 1024, 1), db = mkdesc(st + 8192, 8192, 1024, 1);
    wg_fence();
#pragma unroll
    for (int k = 0; k < 4; k++) wgmma_gemm_n64(acc, da + k * 2, db + k * 128);
    wg_commit();
    if (c & 3) {
      wg_wait<1>();
      if (elect_one()) mbar_arrive(s_bar + B_EMPTY + ((c - 1) & 3) * 8);
    }
    if (c == 3) {
      wg_wait<0>();
      if (elect_one()) mbar_arrive(s_bar + B_EMPTY + 24);
    }
  }
  wg_wait<0>();
  pin(acc);
  if (elect_one()) { mbar_arrive(s_bar + B_EMPTY + 24); mbar_arrive(s_bar + B_TURN + (code & 3) * 8); }
  int t;
  asm volatile("mov.u32 %0, %%tid.x;" : "=r"(t));
  t &= 127;
  const int lane = t & 31, w4 = t >> 5;
  const int l = code >> 3, r = (code >> 2) & 1, p = code & 3;
  const int rb = blockIdx.x >> 3, ct = blockIdx.x & 7, row0 = tok0(r, rb);
  const uint32_t stg = sbase + M_STG;
  if (p == 0) {
    mbar_wait(s_bar + B_RES, r);
    const uint32_t ra = stg + (w4 * 16 + (lane & 15)) * 128;
    float s0 = 0.f, q0 = 0.f, s1 = 0.f, q1 = 0.f;
#pragma unroll
    for (int j = 0; j < 8; j += 2) {
      const uint32_t a = ra + (((j + (lane >> 4)) ^ (lane & 7)) << 4);
      uint32_t y[4];
      ldsm4(a, y[0], y[1], y[2], y[3]);
#pragma unroll
      for (int e = 0; e < 4; e++) {
        y[e] = hadd2_bf16(y[e], pack_bf16(acc[4 * j + 2 * e], acc[4 * j + 2 * e + 1]));
        const float lo = bf_lo(y[e]), hi = bf_hi(y[e]);
        if (e & 1) { s1 += lo + hi; q1 = fmaf(lo, lo, fmaf(hi, hi, q1)); }
        else { s0 += lo + hi; q0 = fmaf(lo, lo, fmaf(hi, hi, q0)); }
      }
      stsm4(a, y[0], y[1], y[2], y[3]);
    }
    __syncwarp();
    __nv_bfloat16* xout = (l == 3 ? P.out : g_x + (size_t)l * S_ * D_) + (size_t)(row0 + w4 * 16 + (lane >> 3)) * D_ + ct * 64 + (lane & 7) * 8;
#pragma unroll
    for (int i = 0; i < 4; i++) {
      const int rr = i * 4 + (lane >> 3);
      *reinterpret_cast<uint4*>(xout + (size_t)i * 4 * D_) = lds128(stg + (w4 * 16 + rr) * 128 + (((lane & 7) ^ (rr & 7)) << 4));
    }
    if (l < 3) {
#pragma unroll
      for (int o = 1; o < 4; o <<= 1) {
        s0 += __shfl_xor_sync(0xffffffffu, s0, o); q0 += __shfl_xor_sync(0xffffffffu, q0, o);
        s1 += __shfl_xor_sync(0xffffffffu, s1, o); q1 += __shfl_xor_sync(0xffffffffu, q1, o);
      }
      if ((lane & 3) == 0) {
        float2* st = g_stats + ((l + 1) * S_ + row0 + w4 * 16 + (lane >> 2)) * 8 + ct;
        st[0] = make_float2(s0, q0); st[64] = make_float2(s1, q1);
      }
      __syncwarp();
      if (r) cnt_signal(CNT_X + (code >> 2) * 16 + rb);
    }
  } else {
    const bool kv = !(l & 1) && p == 1;
    const int type = p == 3 ? 0 : p;
    mbar_wait(s_bar + B_PRE, r);
    mbar_wait(s_bar + B_EPI + (prev & 3) * 8, (prev >> 2) & 1);
    const float2 st0 = reinterpret_cast<const float2*>(sm + M_ROW)[w4 * 16 + (lane >> 2)];
    const float2 st1 = reinterpret_cast<const float2*>(sm + M_ROW)[w4 * 16 + (lane >> 2) + 8];
    const float* cs = reinterpret_cast<const float*>(sm + M_CS) + (p - 1) * 64 + (lane & 3) * 2;
    const uint32_t saddr = stg + (w4 * 16 + (lane & 15)) * STG_PITCH + (lane >> 4) * 16;
    if (kv) {
      proj_stage<true>(acc, 0, saddr, cs, st0.x, st0.y, st1.x, st1.y);
      proj_stage<false>(acc, 2, saddr, cs, st0.x, st0.y, st1.x, st1.y);
    } else if (type == 2) {
#pragma unroll
      for (int j = 0; j < 8; j += 2) proj_stage<false>(acc, j, saddr, cs, st0.x, st0.y, st1.x, st1.y);
    } else {
      const float sc = type == 0 ? QSCALE : 1.f, f0 = st0.y * sc, f1 = st1.y * sc;
#pragma unroll
      for (int j = 0; j < 8; j += 2) proj_stage<true>(acc, j, saddr, cs, st0.x, f0, st1.x, f1);
    }
    named_sync(wg + 1, 128);
    const int row = t & 63;
#pragma unroll
    for (int i = 0; i < 2; i++) {
      if (kv && i == 1) break;
      const int hh = 2 * i + (t >> 6);
      const uint32_t a = stg + row * STG_PITCH + hh * 32;
      const uint32_t ap = row >= 4 ? a - 4 * STG_PITCH : (r ? sbase + M_KTAIL + row * 128 + hh * 32 : 0u);
      proj_store(a, ap, kv ? 1 + hh : type, l + 1, kv ? 0 : ct * 4 + hh, row0 + row);
    }
    if (p == 1 && r == 0 && t < 32)
      *reinterpret_cast<uint4*>(sm + M_KTAIL + t * 16) = lds128(stg + (60 + (t >> 3)) * STG_PITCH + (t & 7) * 16);
  }
  __syncwarp();
  if (lane == 0) mbar_arrive(s_bar + B_EPI + p * 8);
}

__global__ void __launch_bounds__(640, 1) mega_kernel(const __grid_constant__ MegaParams P) {
  extern __shared__ __align__(1024) uint8_t sm[];
  constexpr uint32_t sbase = 1024;
  if (s2u(sm) != sbase) __trap();
  const uint32_t s_bar = sbase + M_BAR;
  const int tid = threadIdx.x, warp = tid >> 5, lane = tid & 31;
  TM(2, 0);
  if (tid == 0) {
    for (int i = 0; i < 4; i++) {
      mbar_init(s_bar + B_FULL + i * 8, 1); mbar_init(s_bar + B_EMPTY + i * 8, 4);
      mbar_init(s_bar + B_TURN + i * 8, 4); mbar_init(s_bar + B_EPI + i * 8, 4);
    }
    for (int i = 0; i < 2; i++) { mbar_init(s_bar + B_KV + i * 8, 1); mbar_init(s_bar + B_Q + i * 8, 1); mbar_init(s_bar + B_ODONE + i * 8, 16); }
    mbar_init(s_bar + B_FREE0, 16);
    mbar_init(s_bar + B_RES, 1);
    mbar_init(s_bar + B_PRE, 1);
    mbar_init(s_bar + B_CHK, 1);
    fence_bar_init();
  }
  if (tid < 512) *reinterpret_cast<uint4*>(sm + M_KV + 16 * 8192 + tid * 16) = make_uint4(0x3f803f80u, 0x3f803f80u, 0x3f803f80u, 0x3f803f80u);
  fence_async_smem();
  __syncthreads();
  const int wg = __shfl_sync(0xffffffffu, warp >> 2, 0);

  if (wg < 4) {
    asm volatile("setmaxnreg.inc.sync.aligned.u32 112;");
    pdl_wait();
    uint32_t pb = POLY_B;
    asm volatile("" : "+r"(pb));
    float s[32], o[12];
    uint32_t p0[16], p1[16];
#pragma unroll
    for (int i = 0; i < 32; i++) s[i] = ((MUFU_MASK >> (i >> 1)) & 1) ? 0.f : EXP_MAGIC;
#pragma unroll
    for (int i = 0; i < 12; i++) o[i] = 0.f;
    uint64_t dq = mkdesc(sbase + M_Q + wg * 2048, 128, 256, 0);
    uint64_t dk0 = mkdesc(sbase + M_KV + k_unit(0, 0) * 8192, 128, 256, 0), dk1 = mkdesc(sbase + M_KV + k_unit(0, 1) * 8192, 128, 256, 0);
    uint64_t dv = mkdesc(sbase + M_KV + v_unit(0, 0) * 8192, 128, 8192, 0);
    int pass_it = -1;
    mbar_wait_long(s_bar + B_Q, 0);
    mbar_wait_long(s_bar + B_KV, 0);
    TM1(3, 3);
    pin(o);
    att_step<false>(s, o, p1, p0, dq, dk0, dv, pb);
    {
#pragma unroll 1
      for (int it = 0; it < 32; it++) {
        const int b = it & 3;
        pin(o);
        att_step<true>(s, o, p0, p1, dq, dk0 + 128, dv, pb);
        att_step<true>(s, o, p1, p0, dq, dk0 + 256, dv + 64, pb);
        att_step<true>(s, o, p0, p1, dq, dk0 + 384, dv + 128, pb);
        att_step<true>(s, o, p1, p0, dq, dk1, dv + 192, pb);
        att_step<true>(s, o, p0, p1, dq, dk1 + 128, dv + 256, pb);
        att_step<true>(s, o, p1, p0, dq, dk1 + 256, dv + 320, pb);
        att_step<true>(s, o, p0, p1, dq, dk1 + 384, dv + 384, pb);
        wg_wait<0>();
        const uint64_t dvp = dv;
        dk0 -= 2048; dk1 -= 1024; dv += (1024ull << 32) - 2048ull;
        if (it == pass_it || b == 3) {
          const int lr = it >> 2, rnd = lr & 1, layer = lr >> 1, par = layer & 1;
          int t;
          asm volatile("mov.u32 %0, %%tid.x;" : "=r"(t));
          const int ln = t & 31, head = blockIdx.x >> 2;
          const int row0 = (blockIdx.x & 3) * 512 + rnd * 256 + wg * 64;
          pin(p1); pin(o);
          wg_fence();
          pv4(o, p1, dvp + 448);
          wg_commit();
          wg_wait<0>();
          pin(o); pin(s);
          if ((it & 7) == 5 && elect_one()) mbar_arrive(s_bar + B_FREE0);
          int code = (lr - 1) * 4 + ((wg - lr + 1) & 3);
          if (b == 3) {
            __nv_bfloat16* dst = g_o + (size_t)(row0 + ((t >> 5) & 3) * 16 + (ln >> 2)) * D_ + head * 16 + (ln & 3) * 2;
            const float l0 = o[8], l1 = o[10];
            float mx = 0.f;
#pragma unroll
            for (int i = 0; i < 8; i++) mx += fabsf(o[i]);
            const float i0 = __fdividef(1.f, l0), i1 = __fdividef(1.f, l1);
            *reinterpret_cast<uint32_t*>(dst) = pack_bf16(o[0] * i0, o[1] * i0);
            *reinterpret_cast<uint32_t*>(dst + 8) = pack_bf16(o[4] * i0, o[5] * i0);
            *reinterpret_cast<uint32_t*>(dst + 8 * D_) = pack_bf16(o[2] * i1, o[3] * i1);
            *reinterpret_cast<uint32_t*>(dst + 8 * D_ + 8) = pack_bf16(o[6] * i1, o[7] * i1);
            mbar_wait(s_bar + B_CHK, par);
            const bool ok = sm[M_CHK + par * 8 + rnd * 4 + wg] && l0 >= 1e-18f && l0 <= 1e37f &&
                            l1 >= 1e-18f && l1 <= 1e37f && mx <= 3e38f;
            uint32_t bad;
            asm volatile("{.reg .pred p, q; setp.eq.u32 p, %1, 0; barrier.red.or.pred.aligned q, %2, 128, p; selp.u32 %0, 1, 0, q;}"
                         : "=r"(bad) : "r"((uint32_t)ok), "r"(wg + 1) : "memory");
            if (bad) {
              att_fallback(P, layer, head, row0, reinterpret_cast<__nv_bfloat16*>(sm + M_Q + rnd * 8192 + wg * 2048), wg + 1);
              fence_async_smem();
            }
            __syncwarp();
            if (elect_one()) mbar_arrive(s_bar + B_ODONE + rnd * 8);
            if (rnd) cnt_signal(CNT_O + lr * 16 + (blockIdx.x & 3) * 4 + wg);
#pragma unroll
            for (int i = 0; i < 32; i++) s[i] = ((MUFU_MASK >> (i >> 1)) & 1) ? 0.f : EXP_MAGIC;
#pragma unroll
            for (int i = 0; i < 12; i++) o[i] = 0.f;
            const int pp = (wg - lr) & 3;
            code = pp == 0 ? lr * 4 : -1;
            pass_it = pp > 0 && pass_exists(lr, pp) ? it + ((rnd || pp == 1) ? 2 : 3) : -1;
            dq += rnd ? -512ll : 512ll;
            dk0 += 4 * 2048; dk1 += 4 * 1024; dv -= (4096ull << 32) - 4 * 2048ull;
          }
          if (code >= 0) {
            TM3(24 + code, 0);
            proj_pass(P, sm, sbase, code, wg);
            TM3(24 + code, 1);
          }
          if (it == 31) break;
          if (b & 1) {
            if (HOLD && (it & 7) == 7 && ((wg - lr) & 3) <= HOLD) mbar_wait_long(s_bar + B_TURN, 1);
          if (b == 3) mbar_wait_long(s_bar + B_Q + (~it & 4) * 2, ((it + 1) >> 3) & 1);
            mbar_wait_long(s_bar + B_KV + (~b & 2) * 4, ((it + 1) >> 3) & 1);
            if (b == 3) TM1(3 + ((it + 1) >> 2), 3);
          }
          pin(o);
          att_step<false>(s, o, p1, p0, dq, dk0, dv, pb);
        } else {
          if (b == 1) {
            TM1(3 + (it >> 2), 4);
            mbar_wait_long(s_bar + B_KV + 8, (it >> 3) & 1);
            TM1(3 + (it >> 2), 5);
          }
          att_step<true>(s, o, p1, p0, dq, dk0, dvp + 448, pb);
          wg_wait<0>();
          if ((it & 7) == 5 && elect_one()) mbar_arrive(s_bar + B_FREE0);
        }
      }
    }
  } else {
    asm volatile("setmaxnreg.dec.sync.aligned.u32 32;");
    const int w4 = __shfl_sync(0xffffffffu, warp & 3, 0);
    const int rb = blockIdx.x >> 3, ct = blockIdx.x & 7;
    if (EXP_NIT < 32 && EXP_AUX == 0) {
      if (w4 == 2) { pdl_wait(); load_q(sbase, 0, 0); load_kv(sbase, 0, 0); load_kv(sbase, 0, 1); load_q(sbase, 0, 1); }
    } else if (EXP_NIT < 32) {
      if (w4 == 2) { pdl_wait(); load_q(sbase, 0, 0); load_kv(sbase, 0, 0); load_kv(sbase, 0, 1); load_q(sbase, 0, 1); }
      mbar_wait_long(s_bar + B_ODONE + 8, 0);
    } else if (w4 == 0) {
      int code = 0;
      bool gated = true;
#pragma unroll 1
      while (code < 32) {
        code = __shfl_sync(0xffffffffu, code, 0);
        const int job = code >> 2, p = code & 3;
        const CUtensorMap* mb = b_map(P, code);
        const CUtensorMap* ma = &P.m[p == 0 ? 1 : 0];
        const int colb = b_col(code), rowa = tok0(job & 1, rb) + (p == 0 ? 0 : (code >> 3) * S_);
#pragma unroll 1
        for (int c = 0; c < 4; c++) {
          if (code > 0) mbar_wait(s_bar + B_EMPTY + c * 8, 1);
          if (elect_one()) {
            issue_b(sbase, mb, colb, c, c);
            if (!gated) issue_a(sbase, ma, rowa, c, c);
          }
        }
        if (gated) {
          if (p == 0) {
            if (code == 0) pdl_wait();
            else { const int prev = prev_pass(code); mbar_wait_long(s_bar + B_EPI + (prev & 3) * 8, (prev >> 2) & 1); }
            if (elect_one()) {
              asm volatile("fence.proxy.async;" ::: "memory");
              mbar_expect(s_bar + B_RES, 8192);
              tma_load(sbase + M_STG, &P.m[job < 2 ? 7 : 0], ct * 64, tok0(job & 1, rb) + (job < 2 ? 0 : ((job >> 1) - 1) * S_), s_bar + B_RES);
            }
            mbar_wait_long(s_bar + B_ODONE + (job & 1) * 8, (job >> 1) & 1);
            cnt_wait(CNT_O + job * 16 + rb, 128);
            TM2(12 + job, 1);
          } else {
            mbar_wait_long(s_bar + B_EPI, job & 1);
            cnt_wait(CNT_X + job * 16 + rb, 32);
            TM2(12 + job, 3);
          }
          if (elect_one()) {
#pragma unroll
            for (int c = 0; c < 4; c++) issue_a(sbase, ma, rowa, c, c);
          }
        }
#pragma unroll 1
        for (int c = 0; c < 4; c++) {
          mbar_wait(s_bar + B_EMPTY + c * 8, 0);
          if (elect_one()) {
            issue_b(sbase, mb, colb, c, c + 4);
            issue_a(sbase, ma, rowa, c, c + 4);
          }
        }
        code = next_pass(code);
        gated = p == 0 || (code & 3) == 0;
      }
    } else if (w4 == 1) {
#pragma unroll 1
      for (int job = 0; job < 8; job++) {
        mbar_wait_long(s_bar + B_ODONE + (job & 1) * 8, (job >> 1) & 1);
        if (!(job & 1)) {
          asm volatile("fence.acq_rel.gpu;" ::: "memory");
          if (lane < 4) asm volatile("red.relaxed.gpu.global.add.u32 [%0], 4;" ::"l"(g_cnt + CNT_O + job * 16 + (blockIdx.x & 3) * 4 + lane) : "memory");
        }
        if (job >= 6) continue;
        mbar_wait_long(s_bar + B_EPI, job & 1);
        if (!(job & 1)) cnt_signal(CNT_X + job * 16 + rb, 4);
        if (pass_exists(job, 1)) {
          mbar_wait_long(s_bar + B_EPI + 8, job & 1);
          if (job & 2) mbar_wait_long(s_bar + B_EPI + 16, job & 1);
          cnt_signal(CNT_KV + job * 8 + ct);
        }
        mbar_wait_long(s_bar + B_EPI + 24, job & 1);
        cnt_signal(CNT_Q + (job * 4 + (rb >> 2)) * 8 + ct);
      }
    } else if (w4 == 2) {
      pdl_wait();
      load_q(sbase, 0, 0); load_kv(sbase, 0, 0); load_kv(sbase, 0, 1); load_q(sbase, 0, 1);
#pragma unroll 1
      for (int job = 0; job < 6; job++) {
        const int l = job >> 1, r = job & 1;
        mbar_wait_long(s_bar + B_ODONE + r * 8, l & 1);
        if (r == 0) mbar_wait_long(s_bar + B_FREE0, l & 1);
        mbar_wait_long(s_bar + B_TURN, job & 1);
        cnt_wait(CNT_KV + job * 8 + ((l & 1) ? blockIdx.x >> 4 : 0), 16);
        load_kv(sbase, l + 1, r);
        cnt_wait(CNT_Q + (job * 4 + (blockIdx.x & 3)) * 8 + (blockIdx.x >> 4), 4);
        load_q(sbase, l + 1, r);
      }
    } else {
      pdl_wait();
#pragma unroll 1
      for (int job = -1; job < 6; job++) {
        if (job & 1) {
          const int l = (job + 1) >> 1, head = blockIdx.x >> 2;
          if (job > 0) { mbar_wait_long(s_bar + B_KV + 8, l & 1); mbar_wait_long(s_bar + B_Q + 8, l & 1); }
          const float* nk = g_nrm + ((l * 2 + 1) * H_ + ((l & 1) ? 0 : head)) * 64;
          const unsigned q = __float_as_uint(__ldcg(g_nrm + (l * 2 * H_ + head) * 64 + (blockIdx.x & 3) * 16 + (lane & 15)));
          const unsigned kn = __reduce_max_sync(0xffffffffu, max(__float_as_uint(__ldcg(nk + lane)), __float_as_uint(__ldcg(nk + 32 + lane))));
          const unsigned qn = max(q, __shfl_xor_sync(0xffffffffu, q, 1));
          if (lane < 16 && !(lane & 1))
            sm[M_CHK + (l & 1) * 8 + (lane >> 1)] = __uint_as_float(qn) * __uint_as_float(kn) <= SCORE_LIMIT * SCORE_LIMIT;
          __syncwarp();
          if (elect_one()) mbar_arrive(s_bar + B_CHK);
        }
        if (job == 5) break;
        job++;
        float c[6];
#pragma unroll
        for (int i = 0; i < 6; i++) {
          const int p = 1 + (i >> 1);
          c[i] = __ldcg(g_colsum + ((job & 2) ? (p == 3 ? 0 : p * 512) + ct * 64 : (p == 3 ? 1536 + ct * 64 : 2048)) + (i & 1) * 32 + lane);
        }
        mbar_wait_long(s_bar + B_TURN, job & 1);
#pragma unroll
        for (int i = 0; i < 6; i++) reinterpret_cast<float*>(sm + M_CS)[i * 32 + lane] = c[i];
        __syncwarp();
        if (elect_one()) mbar_arrive(s_bar + B_PRE);
        job--;
      }
    }
    named_sync(5, 128);
    if (tid == 512) {
      unsigned old;
      asm volatile("atom.acq_rel.gpu.global.add.u32 %0, [%1], 1;" : "=r"(old) : "l"(g_cnt + CNT_DONE) : "memory");
      if (old == gridDim.x - 1)
        for (int i = 0; i < CNT_N; i++) g_cnt[i] = 0u;
    }
  }
}

typedef CUresult (*EncodeFn)(CUtensorMap*, CUtensorMapDataType, cuuint32_t, void*, const cuuint64_t*, const cuuint64_t*,
                             const cuuint32_t*, const cuuint32_t*, CUtensorMapInterleave, CUtensorMapSwizzle,
                             CUtensorMapL2promotion, CUtensorMapFloatOOBfill);

void make_map(EncodeFn enc, CUtensorMap* m, const void* p, int rows, int cols) {
  cuuint64_t dim[2] = {(cuuint64_t)cols, (cuuint64_t)rows};
  cuuint64_t str[1] = {(cuuint64_t)cols * 2};
  cuuint32_t box[2] = {64, 64};
  cuuint32_t es[2] = {1, 1};
  enc(m, CU_TENSOR_MAP_DATA_TYPE_BFLOAT16, 2, const_cast<void*>(p), dim, str, box, es, CU_TENSOR_MAP_INTERLEAVE_NONE,
      CU_TENSOR_MAP_SWIZZLE_128B, CU_TENSOR_MAP_L2_PROMOTION_L2_128B, CU_TENSOR_MAP_FLOAT_OOB_FILL_NONE);
}

template <typename... KA, typename... A>
void launch(void (*k)(KA...), int grid, int block, int smem, bool pdl, A... args) {
  cudaLaunchConfig_t cfg = {};
  cfg.gridDim = dim3(grid); cfg.blockDim = dim3(block); cfg.dynamicSmemBytes = smem; cfg.stream = cudaStreamPerThread;
  cudaLaunchAttribute at[1];
  at[0].id = cudaLaunchAttributeProgrammaticStreamSerialization;
  at[0].val.programmaticStreamSerializationAllowed = 1;
  cfg.attrs = at; cfg.numAttrs = pdl ? 1 : 0;
  cudaLaunchKernelEx(&cfg, k, KA(args)...);
}

struct HostState {
  bool init;
  const void* in[8];
  MegaParams mp;
};
HostState hs;

}

extern "C" void kernel_launch(void* const* d_in, const int* in_sizes, int n_in, void* d_out, int out_size) {
  const __nv_bfloat16* A_x = (const __nv_bfloat16*)d_in[0];
  const __nv_bfloat16* A_wqkv = (const __nv_bfloat16*)d_in[1];
  const __nv_bfloat16* A_wo = (const __nv_bfloat16*)d_in[2];
  const __nv_bfloat16* B_wq = (const __nv_bfloat16*)d_in[4];
  const __nv_bfloat16* B_wk = (const __nv_bfloat16*)d_in[5];
  const __nv_bfloat16* B_wv = (const __nv_bfloat16*)d_in[6];
  const __nv_bfloat16* B_wo = (const __nv_bfloat16*)d_in[7];
  bool same = hs.init;
  for (int i = 0; i < 8; i++) same = same && hs.in[i] == d_in[i];
  if (!same) {
    void* fn = nullptr;
    cudaDriverEntryPointQueryResult qr;
    cudaGetDriverEntryPoint("cuTensorMapEncodeTiled", &fn, cudaEnableDefault, &qr);
    EncodeFn enc = (EncodeFn)fn;
    void *px, *po, *pw;
    cudaGetSymbolAddress(&px, g_x);
    cudaGetSymbolAddress(&po, g_o);
    cudaGetSymbolAddress(&pw, g_wkv);
    make_map(enc, &hs.mp.m[7], A_x, S_, D_);
    make_map(enc, &hs.mp.m[0], px, 3 * S_, D_);
    make_map(enc, &hs.mp.m[1], po, S_, D_);
    make_map(enc, &hs.mp.m[2], A_wqkv, D_, 1536);
    make_map(enc, &hs.mp.m[3], B_wq, D_, 512);
    make_map(enc, &hs.mp.m[4], pw, D_, 32);
    make_map(enc, &hs.mp.m[5], A_wo, D_, D_);
    make_map(enc, &hs.mp.m[6], B_wo, D_, D_);
    hs.mp.x0 = A_x; hs.mp.wqkv = A_wqkv; hs.mp.wq = B_wq; hs.mp.wk = B_wk;
    cudaFuncSetAttribute(prep_kernel, cudaFuncAttributePreferredSharedMemoryCarveout, 100);
    cudaFuncSetAttribute(g1a_kernel, cudaFuncAttributeMaxDynamicSharedMemorySize, G1A_SMEM);
    cudaFuncSetAttribute(mega_kernel, cudaFuncAttributeMaxDynamicSharedMemorySize, MEGA_SMEM);
    for (int i = 0; i < 8; i++) hs.in[i] = d_in[i];
    hs.init = true;
  }
  hs.mp.out = (__nv_bfloat16*)d_out;
  launch(prep_kernel, 130, 256, 0, false, A_x, A_wqkv, B_wq, B_wk, B_wv);
  launch(g1a_kernel, 128, 288, G1A_SMEM, true, hs.mp.m[7], hs.mp.m[2]);
  launch(mega_kernel, 128, 640, MEGA_SMEM, true, hs.mp);
}
```

```cpp
#include <cuda_runtime.h>
#include <cuda_bf16.h>
#include <cuda_fp16.h>
#include <cuda.h>
#include <stdint.h>

namespace {

constexpr int S_ = 2048, D_ = 512, H_ = 32;

__device__ __align__(1024) __nv_bfloat16 g_x[3 * S_ * D_];
__device__ __align__(1024) __nv_bfloat16 g_o[S_ * D_];
__device__ __align__(1024) uint4 g_q[2 * H_ * S_ * 2];
__device__ __align__(1024) uint4 g_k[2 * H_ * S_ * 2];
__device__ __align__(1024) uint4 g_v[2 * H_ * S_ * 2];
__device__ __align__(1024) __nv_bfloat16 g_wkv[D_ * 32];
__device__ __align__(16) float2 g_stats[4 * S_ * 8];
__device__ __align__(16) float g_colsum[1536 + 512 + 64];
__device__ float g_nrm[4 * 2 * H_ * 64];
constexpr int CNT_O = 0, CNT_X = 128, CNT_KV = CNT_X + 128, CNT_Q = CNT_KV + 64, CNT_DONE = CNT_Q + 256, CNT_N = CNT_DONE + 1;
__device__ unsigned g_cnt[CNT_N];

#define EXP_NIT 32
#define EXP_AUX 0
#define TM(k, slot)
#define TM1(k, slot)
#define TM2(k, slot)
#define TM3(k, slot)
__device__ __forceinline__ uint32_t s2u(const void* p) { return (uint32_t)__cvta_generic_to_shared(p); }
__device__ __forceinline__ void mbar_init(uint32_t bar, int cnt) {
  asm volatile("mbarrier.init.shared::cta.b64 [%0], %1;" ::"r"(bar), "r"(cnt) : "memory");
}
__device__ __forceinline__ void mbar_expect(uint32_t bar, uint32_t bytes) {
  asm volatile("mbarrier.arrive.expect_tx.shared::cta.b64 _, [%0], %1;" ::"r"(bar), "r"(bytes) : "memory");
}
__device__ __forceinline__ void mbar_arrive(uint32_t bar) {
  asm volatile("mbarrier.arrive.shared::cta.b64 _, [%0];" ::"r"(bar) : "memory");
}
__device__ __forceinline__ void mbar_wait(uint32_t bar, uint32_t par) {
  uint32_t ok;
  int it = 0;
  do {
    asm volatile("{.reg .pred p; mbarrier.try_wait.parity.shared::cta.b64 p, [%1], %2; selp.u32 %0,1,0,p;}"
                 : "=r"(ok) : "r"(bar), "r"(par) : "memory");
    if (++it > (1 << 24)) __trap();
  } while (!ok);
}
#define SLEEP_NS 32
__device__ __forceinline__ void mbar_wait_long(uint32_t bar, uint32_t par) {
  uint32_t ok;
  int it = 0;
  while (true) {
    asm volatile("{.reg .pred p; mbarrier.test_wait.parity.shared::cta.b64 p, [%1], %2; selp.u32 %0,1,0,p;}"
                 : "=r"(ok) : "r"(bar), "r"(par) : "memory");
    if (ok) break;
    if (++it > (1 << 24)) __trap();
    __nanosleep(SLEEP_NS);
  }
}
__device__ __forceinline__ void bulk_load(uint32_t dst, const void* src, uint32_t bytes, uint32_t bar) {
  asm volatile("cp.async.bulk.shared::cluster.global.mbarrier::complete_tx::bytes [%0], [%1], %2, [%3];"
               ::"r"(dst), "l"(src), "r"(bytes), "r"(bar) : "memory");
}
__device__ __forceinline__ void tma_load(uint32_t dst, const CUtensorMap* m, int c0, int c1, uint32_t bar) {
  asm volatile("cp.async.bulk.tensor.2d.shared::cluster.global.mbarrier::complete_tx::bytes [%0], [%1, {%3, %4}], [%2];"
               ::"r"(dst), "l"(m), "r"(bar), "r"(c0), "r"(c1) : "memory");
}
__device__ __forceinline__ bool elect_one() {
  uint32_t p;
  asm volatile("{.reg .pred q; elect.sync _|q, 0xffffffff; selp.u32 %0, 1, 0, q;}" : "=r"(p));
  return p;
}
__device__ __forceinline__ void pdl_wait() { asm volatile("griddepcontrol.wait;" ::: "memory"); }
__device__ __forceinline__ void pdl_launch() { asm volatile("griddepcontrol.launch_dependents;" ::: "memory"); }
__device__ __forceinline__ void fence_async_smem() { asm volatile("fence.proxy.async.shared::cta;" ::: "memory"); }
__device__ __forceinline__ void fence_bar_init() { asm volatile("fence.mbarrier_init.release.cluster;" ::: "memory"); }
__device__ __forceinline__ void named_sync(int id, int n) { asm volatile("bar.sync %0, %1;" ::"r"(id), "r"(n) : "memory"); }
__device__ __forceinline__ void wg_fence() { asm volatile("wgmma.fence.sync.aligned;" ::: "memory"); }
__device__ __forceinline__ void wg_commit() { asm volatile("wgmma.commit_group.sync.aligned;" ::: "memory"); }
template <int N> __device__ __forceinline__ void wg_wait() { asm volatile("wgmma.wait_group.sync.aligned %0;" ::"n"(N) : "memory"); }
template <int N> __device__ __forceinline__ void pin(float (&d)[N]) {
#pragma unroll
  for (int i = 0; i < N; i++) asm volatile("" : "+f"(d[i])::"memory");
}
template <int N> __device__ __forceinline__ void pin(uint32_t (&d)[N]) {
#pragma unroll
  for (int i = 0; i < N; i++) asm volatile("" : "+r"(d[i])::"memory");
}
__device__ __forceinline__ uint64_t mkdesc(uint32_t addr, uint32_t lbo, uint32_t sbo, uint64_t swz) {
  return (uint64_t)((addr & 0x3FFFF) >> 4) | ((uint64_t)(lbo >> 4) << 16) | ((uint64_t)(sbo >> 4) << 32) | (swz << 62);
}
__device__ __forceinline__ uint32_t pack_bf16(float lo, float hi) {
  uint32_t d; asm("cvt.rn.bf16x2.f32 %0, %1, %2;" : "=r"(d) : "f"(hi), "f"(lo)); return d;
}
__device__ __forceinline__ uint32_t pack_f16(float lo, float hi) {
  uint32_t d; asm("cvt.rn.f16x2.f32 %0, %1, %2;" : "=r"(d) : "f"(hi), "f"(lo)); return d;
}
__device__ __forceinline__ float bf_lo(uint32_t v) { return __uint_as_float(v << 16); }
__device__ __forceinline__ float bf_hi(uint32_t v) { return __uint_as_float(v & 0xffff0000u); }
__device__ __forceinline__ void stsm4(uint32_t addr, uint32_t a, uint32_t b, uint32_t c, uint32_t d) {
  asm volatile("stmatrix.sync.aligned.m8n8.x4.shared.b16 [%0], {%1,%2,%3,%4};" ::"r"(addr), "r"(a), "r"(b), "r"(c), "r"(d) : "memory");
}
__device__ __forceinline__ void ldsm4(uint32_t addr, uint32_t& a, uint32_t& b, uint32_t& c, uint32_t& d) {
  asm volatile("ldmatrix.sync.aligned.m8n8.x4.shared.b16 {%0,%1,%2,%3}, [%4];" : "=r"(a), "=r"(b), "=r"(c), "=r"(d) : "r"(addr) : "memory");
}
__device__ __forceinline__ uint32_t hadd2_bf16(uint32_t a, uint32_t b) {
  uint32_t d; asm("add.rn.bf16x2 %0, %1, %2;" : "=r"(d) : "r"(a), "r"(b)); return d;
}
__device__ __forceinline__ uint4 lds128(uint32_t addr) {
  uint4 v; asm volatile("ld.shared.v4.u32 {%0,%1,%2,%3}, [%4];" : "=r"(v.x), "=r"(v.y), "=r"(v.z), "=r"(v.w) : "r"(addr) : "memory"); return v;
}

__device__ __forceinline__ void wgmma_qk_n64(float (&d)[32], uint64_t da, uint64_t db) {
  asm volatile("wgmma.mma_async.sync.aligned.m64n64k16.f32.f16.f16 "
      "{%0,%1,%2,%3,%4,%5,%6,%7,%8,%9,%10,%11,%12,%13,%14,%15,%16,%17,%18,%19,%20,%21,%22,%23,%24,%25,%26,%27,%28,%29,%30,%31}, "
      "%32, %33, 1, 1, 1, 0, 0;"
    : "+f"(d[0]), "+f"(d[1]), "+f"(d[2]), "+f"(d[3]), "+f"(d[4]), "+f"(d[5]), "+f"(d[6]), "+f"(d[7]), "+f"(d[8]),
      "+f"(d[9]), "+f"(d[10]), "+f"(d[11]), "+f"(d[12]), "+f"(d[13]), "+f"(d[14]), "+f"(d[15]), "+f"(d[16]),
      "+f"(d[17]), "+f"(d[18]), "+f"(d[19]), "+f"(d[20]), "+f"(d[21]), "+f"(d[22]), "+f"(d[23]), "+f"(d[24]),
      "+f"(d[25]), "+f"(d[26]), "+f"(d[27]), "+f"(d[28]), "+f"(d[29]), "+f"(d[30]), "+f"(d[31])
    : "l"(da), "l"(db));
}
__device__ __forceinline__ void wgmma_pv_n24(float (&d)[12], uint32_t a0, uint32_t a1, uint32_t a2, uint32_t a3, uint64_t db) {
  asm volatile("wgmma.mma_async.sync.aligned.m64n24k16.f32.bf16.bf16 "
      "{%0,%1,%2,%3,%4,%5,%6,%7,%8,%9,%10,%11}, "
      "{%12,%13,%14,%15}, %16, 1, 1, 1, 1;"
    : "+f"(d[0]), "+f"(d[1]), "+f"(d[2]), "+f"(d[3]), "+f"(d[4]), "+f"(d[5]), "+f"(d[6]), "+f"(d[7]), "+f"(d[8]),
      "+f"(d[9]), "+f"(d[10]), "+f"(d[11])
    : "r"(a0), "r"(a1), "r"(a2), "r"(a3), "l"(db));
}
__device__ __forceinline__ void wgmma_gemm_n64(float (&d)[32], uint64_t da, uint64_t db) {
  asm volatile("wgmma.mma_async.sync.aligned.m64n64k16.f32.bf16.bf16 "
      "{%0,%1,%2,%3,%4,%5,%6,%7,%8,%9,%10,%11,%12,%13,%14,%15,%16,%17,%18,%19,%20,%21,%22,%23,%24,%25,%26,%27,%28,%29,%30,%31}, "
      "%32, %33, 1, 1, 1, 0, 1;"
    : "+f"(d[0]), "+f"(d[1]), "+f"(d[2]), "+f"(d[3]), "+f"(d[4]), "+f"(d[5]), "+f"(d[6]), "+f"(d[7]), "+f"(d[8]),
      "+f"(d[9]), "+f"(d[10]), "+f"(d[11]), "+f"(d[12]), "+f"(d[13]), "+f"(d[14]), "+f"(d[15]), "+f"(d[16]),
      "+f"(d[17]), "+f"(d[18]), "+f"(d[19]), "+f"(d[20]), "+f"(d[21]), "+f"(d[22]), "+f"(d[23]), "+f"(d[24]),
      "+f"(d[25]), "+f"(d[26]), "+f"(d[27]), "+f"(d[28]), "+f"(d[29]), "+f"(d[30]), "+f"(d[31])
    : "l"(da), "l"(db));
}
__device__ __forceinline__ void wgmma_gemm_n32(float (&d)[16], uint64_t da, uint64_t db) {
  asm volatile("wgmma.mma_async.sync.aligned.m64n32k16.f32.bf16.bf16 "
      "{%0,%1,%2,%3,%4,%5,%6,%7,%8,%9,%10,%11,%12,%13,%14,%15}, "
      "%16, %17, 1, 1, 1, 0, 1;"
    : "+f"(d[0]), "+f"(d[1]), "+f"(d[2]), "+f"(d[3]), "+f"(d[4]), "+f"(d[5]), "+f"(d[6]), "+f"(d[7]), "+f"(d[8]),
      "+f"(d[9]), "+f"(d[10]), "+f"(d[11]), "+f"(d[12]), "+f"(d[13]), "+f"(d[14]), "+f"(d[15])
    : "l"(da), "l"(db));
}
__device__ __forceinline__ void wgmma_gemm_n192(float (&d)[96], uint64_t da, uint64_t db) {
  asm volatile("wgmma.mma_async.sync.aligned.m64n192k16.f32.bf16.bf16 "
      "{%0,%1,%2,%3,%4,%5,%6,%7,%8,%9,%10,%11,%12,%13,%14,%15,%16,%17,%18,%19,%20,%21,%22,%23,%24,%25,%26,%27,%28,%29,%30,%31,%32,%33,%34,%35,%36,%37,%38,%39,%40,%41,%42,%43,%44,%45,%46,%47,%48,%49,%50,%51,%52,%53,%54,%55,%56,%57,%58,%59,%60,%61,%62,%63,%64,%65,%66,%67,%68,%69,%70,%71,%72,%73,%74,%75,%76,%77,%78,%79,%80,%81,%82,%83,%84,%85,%86,%87,%88,%89,%90,%91,%92,%93,%94,%95}, "
      "%96, %97, 1, 1, 1, 0, 1;"
    : "+f"(d[0]), "+f"(d[1]), "+f"(d[2]), "+f"(d[3]), "+f"(d[4]), "+f"(d[5]), "+f"(d[6]), "+f"(d[7]), "+f"(d[8]),
      "+f"(d[9]), "+f"(d[10]), "+f"(d[11]), "+f"(d[12]), "+f"(d[13]), "+f"(d[14]), "+f"(d[15]), "+f"(d[16]),
      "+f"(d[17]), "+f"(d[18]), "+f"(d[19]), "+f"(d[20]), "+f"(d[21]), "+f"(d[22]), "+f"(d[23]), "+f"(d[24]),
      "+f"(d[25]), "+f"(d[26]), "+f"(d[27]), "+f"(d[28]), "+f"(d[29]), "+f"(d[30]), "+f"(d[31]), "+f"(d[32]),
      "+f"(d[33]), "+f"(d[34]), "+f"(d[35]), "+f"(d[36]), "+f"(d[37]), "+f"(d[38]), "+f"(d[39]), "+f"(d[40]),
      "+f"(d[41]), "+f"(d[42]), "+f"(d[43]), "+f"(d[44]), "+f"(d[45]), "+f"(d[46]), "+f"(d[47]), "+f"(d[48]),
      "+f"(d[49]), "+f"(d[50]), "+f"(d[51]), "+f"(d[52]), "+f"(d[53]), "+f"(d[54]), "+f"(d[55]), "+f"(d[56]),
      "+f"(d[57]), "+f"(d[58]), "+f"(d[59]), "+f"(d[60]), "+f"(d[61]), "+f"(d[62]), "+f"(d[63]), "+f"(d[64]),
      "+f"(d[65]), "+f"(d[66]), "+f"(d[67]), "+f"(d[68]), "+f"(d[69]), "+f"(d[70]), "+f"(d[71]), "+f"(d[72]),
      "+f"(d[73]), "+f"(d[74]), "+f"(d[75]), "+f"(d[76]), "+f"(d[77]), "+f"(d[78]), "+f"(d[79]), "+f"(d[80]),
      "+f"(d[81]), "+f"(d[82]), "+f"(d[83]), "+f"(d[84]), "+f"(d[85]), "+f"(d[86]), "+f"(d[87]), "+f"(d[88]),
      "+f"(d[89]), "+f"(d[90]), "+f"(d[91]), "+f"(d[92]), "+f"(d[93]), "+f"(d[94]), "+f"(d[95])
    : "l"(da), "l"(db));
}

constexpr float QSCALE = 0.25f * 1.4426950408889634f;
constexpr float LN_EPS = 1e-5f;

__device__ __forceinline__ void row_stats(int layer, int row, float& mu, float& rstd) {
  const float4* p = reinterpret_cast<const float4*>(g_stats + (layer * S_ + row) * 8);
  float4 a = __ldcg(p), b = __ldcg(p + 1), c = __ldcg(p + 2), d = __ldcg(p + 3);
  float s = (a.x + a.z) + (b.x + b.z) + (c.x + c.z) + (d.x + d.z);
  float q = (a.y + a.w) + (b.y + b.w) + (c.y + c.w) + (d.y + d.w);
  mu = s * (1.f / D_);
  float var = fmaxf(q * (1.f / D_) - mu * mu, 0.f);
  rstd = rsqrtf(var + LN_EPS);
}

__global__ void __launch_bounds__(256) prep_kernel(const __nv_bfloat16* __restrict__ x, const __nv_bfloat16* __restrict__ wqkv,
                                                   const __nv_bfloat16* __restrict__ wq, const __nv_bfloat16* __restrict__ wk,
                                                   const __nv_bfloat16* __restrict__ wv) {
  TM(0, 0);
  pdl_launch();
  __shared__ float red[8][16];
  const int b = blockIdx.x, tid = threadIdx.x, lane = tid & 31, warp = tid >> 5;
  {
    const __nv_bfloat16* w; int ld, out;
    if (b < 96) { w = wqkv + b * 16; ld = 1536; out = b * 16; }
    else if (b < 128) { w = wq + (b - 96) * 16; ld = 512; out = 1536 + (b - 96) * 16; }
    else { w = (b == 128) ? wk : wv; ld = 16; out = 2048 + (b - 128) * 16; }
    const int half = tid & 1, r0 = tid >> 1;
    float acc[8];
#pragma unroll
    for (int i = 0; i < 8; i++) acc[i] = 0.f;
#pragma unroll
    for (int j = 0; j < 4; j++) {
      uint4 v = __ldg(reinterpret_cast<const uint4*>(w + (size_t)(r0 + 128 * j) * ld + half * 8));
      if (b >= 128) *reinterpret_cast<uint4*>(g_wkv + (r0 + 128 * j) * 32 + (b - 128) * 16 + half * 8) = v;
      acc[0] += bf_lo(v.x); acc[1] += bf_hi(v.x); acc[2] += bf_lo(v.y); acc[3] += bf_hi(v.y);
      acc[4] += bf_lo(v.z); acc[5] += bf_hi(v.z); acc[6] += bf_lo(v.w); acc[7] += bf_hi(v.w);
    }
#pragma unroll
    for (int i = 0; i < 8; i++) {
#pragma unroll
      for (int o = 2; o < 32; o <<= 1) acc[i] += __shfl_xor_sync(0xffffffffu, acc[i], o);
    }
    if (lane < 2) {
#pragma unroll
      for (int i = 0; i < 8; i++) red[warp][lane * 8 + i] = acc[i];
    }
    __syncthreads();
    if (tid < 16) {
      float s = 0.f;
#pragma unroll
      for (int w8 = 0; w8 < 8; w8++) s += red[w8][tid];
      g_colsum[out + tid] = s;
    }
    if (b == 129 && tid >= 32 && tid < 64) g_colsum[2048 + tid] = 0.f;
  }
  if (b < 128) {
#pragma unroll
    for (int j = 0; j < 2; j++) {
      const int row = b * 16 + warp * 2 + j;
      const uint4* p = reinterpret_cast<const uint4*>(x + (size_t)row * D_ + lane * 16);
      uint4 v0 = __ldg(p), v1 = __ldg(p + 1);
      uint32_t u[8] = {v0.x, v0.y, v0.z, v0.w, v1.x, v1.y, v1.z, v1.w};
      float s = 0.f, q = 0.f;
#pragma unroll
      for (int i = 0; i < 8; i++) {
        float a = bf_lo(u[i]), c = bf_hi(u[i]);
        s += a + c; q = fmaf(a, a, fmaf(c, c, q));
      }
      s += __shfl_xor_sync(0xffffffffu, s, 1); q += __shfl_xor_sync(0xffffffffu, q, 1);
      s += __shfl_xor_sync(0xffffffffu, s, 2); q += __shfl_xor_sync(0xffffffffu, q, 2);
      if ((lane & 3) == 0) g_stats[row * 8 + (lane >> 2)] = make_float2(s, q);
    }
  }
  TM(0, 4);
}

__device__ __forceinline__ int tok0(int r, int rb) { return (rb >> 2) * 512 + r * 256 + (rb & 3) * 64; }
__device__ __forceinline__ int key_pos(int token) {
  const int r = (token >> 8) & 1, rb = ((token >> 9) << 2) | ((token >> 6) & 3), row = token & 63;
  return (16 * r + (row >> 2)) * 64 + rb * 4 + (row & 3);
}
__device__ __forceinline__ float sq_norm16(const uint4& a, const uint4& b) {
  const uint32_t u[8] = {a.x, a.y, a.z, a.w, b.x, b.y, b.z, b.w};
  __half2 n = __hmul2(*reinterpret_cast<const __half2*>(&u[0]), *reinterpret_cast<const __half2*>(&u[0]));
#pragma unroll
  for (int i = 1; i < 8; i++) n = __hfma2(*reinterpret_cast<const __half2*>(&u[i]), *reinterpret_cast<const __half2*>(&u[i]), n);
  return __low2float(n) + __high2float(n);
}
__device__ __forceinline__ uint32_t hsub2(uint32_t a, uint32_t b) {
  uint32_t d; asm("sub.rn.f16x2 %0, %1, %2;" : "=r"(d) : "r"(a), "r"(b)); return d;
}
__device__ __forceinline__ void proj_store(uint32_t a, uint32_t ap, int type, int layer, int head, int token) {
  const uint4 v0 = lds128(a), v1 = lds128(a + 16);
  const size_t hb = (size_t)((layer & 1) * H_ + head) * (S_ * 2);
  if (type == 2) {
    uint4* dst = g_v + hb + key_pos(token);
    dst[0] = v0; dst[S_] = v1;
    return;
  }
  if (type == 0) {
    uint4* dst = g_q + hb + (token >> 3) * 16 + (token & 7);
    dst[0] = v0; dst[8] = v1;
  } else {
    uint4 d0 = v0, d1 = v1;
    if (ap) {
      const uint4 p0 = lds128(ap), p1 = lds128(ap + 16);
      d0 = make_uint4(hsub2(v0.x, p0.x), hsub2(v0.y, p0.y), hsub2(v0.z, p0.z), hsub2(v0.w, p0.w));
      d1 = make_uint4(hsub2(v1.x, p1.x), hsub2(v1.y, p1.y), hsub2(v1.z, p1.z), hsub2(v1.w, p1.w));
    }
    const int pos = key_pos(token);
    uint4* dst = g_k + hb + (pos >> 3) * 16 + (pos & 7);
    dst[0] = d0; dst[8] = d1;
  }
  const unsigned m = __reduce_max_sync(0xffffffffu, __float_as_uint(sq_norm16(v0, v1)) & 0x7fffffffu);
  if ((threadIdx.x & 31) == 0) g_nrm[((layer * 2 + type) * H_ + head) * 64 + (token >> 5)] = __uint_as_float(m);
}
template <bool F16, int N>
__device__ __forceinline__ void proj_stage(const float (&acc)[N], int j  , uint32_t addr, const float* cs,
                                           float mu0, float f0, float mu1, float f1) {
  uint32_t r[4];
#pragma unroll
  for (int e = 0; e < 2; e++) {
    const float2 c = *reinterpret_cast<const float2*>(cs + (j + e) * 8);
    const float a0 = fmaf(-mu0, c.x, acc[(j + e) * 4 + 0]) * f0, a1 = fmaf(-mu0, c.y, acc[(j + e) * 4 + 1]) * f0;
    const float a2 = fmaf(-mu1, c.x, acc[(j + e) * 4 + 2]) * f1, a3 = fmaf(-mu1, c.y, acc[(j + e) * 4 + 3]) * f1;
    r[e * 2] = F16 ? pack_f16(a0, a1) : pack_bf16(a0, a1);
    r[e * 2 + 1] = F16 ? pack_f16(a2, a3) : pack_bf16(a2, a3);
  }
  stsm4(addr + j * 16, r[0], r[1], r[2], r[3]);
}

constexpr int G1A_NS = 5, G1A_STAGE = 16384 + 3 * 8192, G1A_PITCH = 400;
constexpr int G1A_SMEM = G1A_NS * G1A_STAGE + 1024 + 192 * 4 + 128;
__global__ void __launch_bounds__(288, 1) g1a_kernel(const __grid_constant__ CUtensorMap mx, const __grid_constant__ CUtensorMap mw) {
  extern __shared__ uint8_t smem_raw[];
  const uint32_t sbase = (s2u(smem_raw) + 1023) & ~1023u;
  const uint32_t s_cs = sbase + G1A_NS * G1A_STAGE, s_bar = s_cs + 192 * 4;
  float* cs = reinterpret_cast<float*>(smem_raw + (s_cs - s2u(smem_raw)));
  const int tid = threadIdx.x, warp = tid >> 5, lane = tid & 31;
  const int nb = blockIdx.x & 7, rb = blockIdx.x >> 3;
  TM(1, 0);
  if (tid == 0) {
    for (int i = 0; i < G1A_NS; i++) { mbar_init(s_bar + i * 8, 1); mbar_init(s_bar + 40 + i * 8, 2); }
    fence_bar_init();
  }
  __syncthreads();
  if (warp == 8) {
    if (lane == 0) {
      for (int c = 0; c < 8; c++) {
        const int s = c < G1A_NS ? c : c - G1A_NS;
        const uint32_t st = sbase + s * G1A_STAGE, bar = s_bar + s * 8;
        if (c >= G1A_NS) mbar_wait(s_bar + 40 + s * 8, 0);
        mbar_expect(bar, G1A_STAGE);
        tma_load(st, &mx, c * 64, tok0(0, rb), bar);
        tma_load(st + 8192, &mx, c * 64, tok0(1, rb), bar);
        for (int j = 0; j < 3; j++) tma_load(st + 16384 + j * 8192, &mw, nb * 192 + j * 64, c * 64, bar);
      }
    }
    return;
  }
  const int wg = warp >> 2;
  float acc[96];
#pragma unroll
  for (int i = 0; i < 96; i++) acc[i] = 0.f;
  pin(acc);
#pragma unroll 1
  for (int c = 0; c < 8; c++) {
    const int s = c < G1A_NS ? c : c - G1A_NS;
    mbar_wait(s_bar + s * 8, c >= G1A_NS);
    if (c == 0) TM(1, 2);
    const uint32_t st = sbase + s * G1A_STAGE;
    const uint64_t da = mkdesc(st + wg * 8192, 16, 1024, 1), db = mkdesc(st + 16384, 8192, 1024, 1);
    wg_fence();
#pragma unroll
    for (int k = 0; k < 4; k++) wgmma_gemm_n192(acc, da + k * 2, db + k * 128);
    wg_commit();
    if (c >= 1 && c <= 3) { wg_wait<1>(); if ((tid & 127) == 0) mbar_arrive(s_bar + 40 + (c - 1) * 8); }
    if (c == 5) {
      pdl_wait();
      pdl_launch();
      if (tid < 192) cs[tid] = __ldcg(g_colsum + nb * 192 + tid);
    }
  }
  float mu0, rs0, mu1, rs1;
  const int row0 = tok0(wg, rb) + (warp & 3) * 16 + (lane >> 2);
  row_stats(0, row0, mu0, rs0); row_stats(0, row0 + 8, mu1, rs1);
  wg_wait<0>();
  pin(acc);
  TM(1, 3);
  named_sync(1, 256);
  {
    const uint32_t addr = sbase + (wg * 64 + (warp & 3) * 16 + (lane & 15)) * G1A_PITCH + (lane >> 4) * 16;
#pragma unroll
    for (int j = 0; j < 24; j += 2) {
      const int type = (nb * 12 + (j >> 1)) >> 5;
      const float sc = type == 0 ? QSCALE : 1.f;
      if (type == 2) proj_stage<false>(acc, j, addr, cs + (lane & 3) * 2, mu0, rs0, mu1, rs1);
      else proj_stage<true>(acc, j, addr, cs + (lane & 3) * 2, mu0, rs0 * sc, mu1, rs1 * sc);
    }
  }
  named_sync(1, 256);
#pragma unroll
  for (int it = 0; it < 6; it++) {
    const int item = warp + it * 8, hh = item >> 2, trow = (item & 3) * 32 + lane;
    const int hg = nb * 12 + hh;
    const uint32_t a = sbase + trow * G1A_PITCH + hh * 32;
    proj_store(a, trow >= 4 ? a - 4 * G1A_PITCH : 0u, hg >> 5, 0, hg & 31, tok0(trow >> 6, rb) + (trow & 63));
  }
  TM(1, 4);
}

constexpr uint32_t MUFU_MASK = 0xF800u;
constexpr float EXP_MAGIC = 383.0f + 0.65f / 128.0f;
constexpr uint32_t POLY_A = 0x5a835a83u, POLY_B = 0x92a192a1u, POLY_C = 0x800b800bu;
constexpr float SCORE_LIMIT = 116.f;

__device__ __forceinline__ void exp_step(const float (&s)[32], uint32_t (&p)[16], uint32_t pb) {
#pragma unroll
  for (int i = 0; i < 16; i++) {
    if ((MUFU_MASK >> i) & 1) {
      float a, b;
      asm("ex2.approx.ftz.f32 %0, %1;" : "=f"(a) : "f"(s[2 * i]));
      asm("ex2.approx.ftz.f32 %0, %1;" : "=f"(b) : "f"(s[2 * i + 1]));
      p[i] = pack_bf16(a, b);
    } else {
      uint32_t z, u, h;
      asm("prmt.b32 %0, %1, %2, 0x6521;" : "=r"(z) : "r"(__float_as_uint(s[2 * i])), "r"(__float_as_uint(s[2 * i + 1])));
      asm("fma.rn.f16x2 %0, %1, %2, %3;" : "=r"(u) : "r"(z & 0x007f007fu), "r"(POLY_A), "r"(pb));
      asm("fma.rn.f16x2 %0, %1, %1, %2;" : "=r"(h) : "r"(u), "r"(POLY_C));
      p[i] = z - h;
    }
  }
}

__device__ __forceinline__ void pv4(float (&o)[12], const uint32_t (&p)[16], uint64_t dv) {
#pragma unroll
  for (int j = 0; j < 4; j++) wgmma_pv_n24(o, p[4 * j], p[4 * j + 1], p[4 * j + 2], p[4 * j + 3], dv + j * 16);
}
template <bool PV>
__device__ __forceinline__ void att_step(float (&s)[32], float (&o)[12], uint32_t (&pin_)[16], uint32_t (&pout)[16], uint64_t dq,
                                         uint64_t dk, uint64_t dv, uint32_t pb) {
  pin(s);
  if (PV) pin(pin_);
  wg_fence();
  wgmma_qk_n64(s, dq, dk);
  wg_commit();
  if (PV) {
#pragma unroll
    for (int j = 0; j < 4; j++) wgmma_pv_n24(o, pin_[4 * j], pin_[4 * j + 1], pin_[4 * j + 2], pin_[4 * j + 3], dv + j * 16);
    wg_commit();
    wg_wait<1>();
  } else {
    wg_wait<0>();
  }
  pin(s);
  exp_step(s, pout, pb);
  pin(pout);
}

constexpr int M_STAGE = 0;
constexpr int M_STG = 65536, STG_PITCH = 144;
constexpr int M_KV = 74752;
constexpr int M_Q = M_KV + 17 * 8192;
constexpr int M_CS = M_Q + 16384, M_KTAIL = M_CS + 768, M_ROW = M_KTAIL + 512, M_BAR = M_ROW + 512;
constexpr int MEGA_SMEM = M_BAR + 256;
__device__ __forceinline__ int k_unit(int b, int j) { return j == 0 ? 12 - 4 * b : 7 - 2 * b; }
__device__ __forceinline__ int v_unit(int b, int j) { return j == 0 ? 14 - 4 * b : 15 - 2 * b; }
constexpr int B_FULL = 0, B_EMPTY = 32, B_KV = 64, B_Q = 80, B_FREE0 = 96, B_ODONE = 104, B_RES = 120, B_PRE = 128,
              B_TURN = 136, B_EPI = 168, B_CHK = 200, M_CHK = M_BAR + 208;

struct MegaParams {
  CUtensorMap m[8];
  const __nv_bfloat16* x0;
  const __nv_bfloat16* wqkv; const __nv_bfloat16* wq; const __nv_bfloat16* wk;
  __nv_bfloat16* out;
};

__device__ __forceinline__ void cnt_signal(int idx, unsigned n = 1) {
  if (elect_one()) asm volatile("red.release.gpu.global.add.u32 [%0], %1;" ::"l"(g_cnt + idx), "r"(n) : "memory");
}
__device__ __forceinline__ void cnt_wait(int idx, unsigned target) {
  unsigned v;
  int it = 0;
  while (true) {
    asm volatile("ld.acquire.gpu.global.u32 %0, [%1];" : "=r"(v) : "l"(g_cnt + idx) : "memory");
    if (v >= target) break;
    if (++it > (1 << 24)) __trap();
  }
  asm volatile("fence.proxy.async.global;" ::: "memory");
}

__device__ __forceinline__ void att_fallback(const MegaParams& P, int layer, int head, int row0, __nv_bfloat16* sk, int bar_id) {
  int t;
  asm volatile("mov.u32 %0, %%tid.x;" : "=r"(t));
  t &= 127;
  const int hf = t & 1;
  asm volatile("" : "+r"(layer), "+r"(head), "+r"(row0));
  const __nv_bfloat16* x = layer == 0 ? P.x0 : g_x + (size_t)(layer - 1) * S_ * D_;
  const bool mqa = layer & 1;
  const __nv_bfloat16* vimg = reinterpret_cast<const __nv_bfloat16*>(g_v + (size_t)((layer & 1) * H_ + (mqa ? 0 : head)) * (S_ * 2));
  float q[16], o[16], acc[16];
  float m = -INFINITY, l = 0.f;
#pragma unroll
  for (int d = 0; d < 16; d++) { o[d] = 0.f; q[d] = 0.f; }
#pragma unroll 1
  for (int ch = -1; ch < 32; ch++) {
    const int token = ch < 0 ? row0 + (t >> 1) : ch * 64 + (t >> 1);
    const __nv_bfloat16* w = ch < 0 ? (mqa ? P.wq : P.wqkv) + head * 16 : (mqa ? P.wk : P.wqkv + 512 + head * 16);
    const int ld = mqa ? (ch < 0 ? 512 : 16) : 1536;
    float mu, rs;
    row_stats(layer, token, mu, rs);
#pragma unroll
    for (int d = 0; d < 16; d++) acc[d] = 0.f;
#pragma unroll 1
    for (int k = hf * 256; k < hf * 256 + 256; k++) {
      const unsigned short xr = __ldcg(reinterpret_cast<const unsigned short*>(x) + (size_t)token * D_ + k);
      const float xn = __bfloat162float(__float2bfloat16((__uint_as_float((uint32_t)xr << 16) - mu) * rs));
#pragma unroll
      for (int d = 0; d < 16; d++) acc[d] = fmaf(xn, __bfloat162float(w[(size_t)k * ld + d]), acc[d]);
    }
#pragma unroll
    for (int d = 0; d < 16; d++) acc[d] = __bfloat162float(__float2bfloat16(acc[d] + __shfl_xor_sync(0xffffffffu, acc[d], 1)));
    if (ch < 0) {
#pragma unroll
      for (int d = 0; d < 16; d++) q[d] = acc[d];
      continue;
    }
    named_sync(bar_id, 128);
    if (hf == 0) {
#pragma unroll
      for (int d = 0; d < 16; d++) sk[(t >> 1) * 16 + d] = __float2bfloat16(acc[d]);
    }
    named_sync(bar_id, 128);
#pragma unroll 1
    for (int j = hf * 32; j < hf * 32 + 32; j++) {
      float sc = 0.f;
#pragma unroll
      for (int d = 0; d < 16; d++) sc = fmaf(q[d], __bfloat162float(sk[j * 16 + d]), sc);
      sc *= 0.25f;
      if (sc > m || sc != sc) {
        const float a = __expf(m - sc);
        l *= a;
#pragma unroll
        for (int d = 0; d < 16; d++) o[d] *= a;
        m = sc;
      }
      const float p = __expf(sc - m);
      l += p;
      const int pos = key_pos(ch * 64 + j);
#pragma unroll
      for (int d = 0; d < 16; d++) {
        const unsigned short vr = __ldcg(reinterpret_cast<const unsigned short*>(vimg) + (d >> 3) * (S_ * 8) + pos * 8 + (d & 7));
        o[d] = fmaf(p, __uint_as_float((uint32_t)vr << 16), o[d]);
      }
    }
  }
  const float m2 = __shfl_xor_sync(0xffffffffu, m, 1), mm = fmaxf(m, m2), a = __expf(m - mm);
  l *= a; l += __shfl_xor_sync(0xffffffffu, l, 1);
  const float inv = 1.f / l;
  __nv_bfloat16* dst = g_o + (size_t)(row0 + (t >> 1)) * D_ + head * 16;
#pragma unroll
  for (int d = 0; d < 16; d++) {
    float v = o[d] * a; v += __shfl_xor_sync(0xffffffffu, v, 1);
    if ((d >> 3) == hf) dst[d] = __float2bfloat16(v * inv);
  }
}

__device__ __forceinline__ const CUtensorMap* b_map(const MegaParams& P, int code) {
  const int l = code >> 3, p = code & 3;
  return &P.m[p == 0 ? 5 + (l & 1) : ((l & 1) ? 2 : (p == 3 ? 3 : 4))];
}
__device__ __forceinline__ int b_col(int code) {
  const int p = code & 3, ct = blockIdx.x & 7;
  return p == 0 || p == 3 ? ct * 64 : ((code & 8) ? p * 512 + ct * 64 : 0);
}
__device__ __forceinline__ void issue_b(uint32_t sbase, const CUtensorMap* m, int col, int st, int c) {
  mbar_expect(sbase + M_BAR + B_FULL + st * 8, 16384);
  tma_load(sbase + M_STAGE + st * 16384 + 8192, m, col, c * 64, sbase + M_BAR + B_FULL + st * 8);
}
__device__ __forceinline__ void issue_a(uint32_t sbase, const CUtensorMap* m, int row, int st, int c) {
  tma_load(sbase + M_STAGE + st * 16384, m, c * 64, row, sbase + M_BAR + B_FULL + st * 8);
}
__device__ __forceinline__ void load_kv(uint32_t sbase, int l, int r) {
  const size_t hb = (size_t)((l & 1) * H_ + ((l & 1) ? 0 : blockIdx.x >> 2)) * 65536;
  const uint8_t* gk = reinterpret_cast<const uint8_t*>(g_k) + hb;
  const uint8_t* gv = reinterpret_cast<const uint8_t*>(g_v) + hb;
  const uint32_t bar = sbase + M_BAR + B_KV + r * 8;
  if (elect_one()) {
    mbar_expect(bar, 65536);
#pragma unroll
    for (int j = 0; j < 2; j++) {
      const int b = r * 2 + j;
      bulk_load(sbase + M_KV + k_unit(b, 0) * 8192, gk + b * 16384, 8192, bar);
      bulk_load(sbase + M_KV + v_unit(b, 0) * 8192, gv + b * 8192, 8192, bar);
      bulk_load(sbase + M_KV + v_unit(b, 1) * 8192, gv + 32768 + b * 8192, 8192, bar);
      bulk_load(sbase + M_KV + k_unit(b, 1) * 8192, gk + b * 16384 + 8192, 8192, bar);
    }
  }
}
__device__ __forceinline__ void load_q(uint32_t sbase, int l, int r) {
  const uint32_t bar = sbase + M_BAR + B_Q + r * 8;
  if (elect_one()) {
    mbar_expect(bar, 8192);
    bulk_load(sbase + M_Q + r * 8192,
              reinterpret_cast<const uint8_t*>(g_q) + (size_t)((l & 1) * H_ + (blockIdx.x >> 2)) * 65536 + (blockIdx.x & 3) * 16384 + r * 8192,
              8192, bar);
  }
}

__device__ __forceinline__ bool pass_exists(int job, int p) {
  return p == 0 || (job < 6 && (p == 3 || (job & 2) || (p == 1 && (blockIdx.x & 7) == 0)));
}
__device__ __forceinline__ int next_pass(int code) {
  const int job = code >> 2, p = code & 3;
  if (p == 0 && pass_exists(job, 1)) return code + 1;
  if (p == 1 && pass_exists(job, 2)) return code + 1;
  if (p < 3 && pass_exists(job, 3)) return job * 4 + 3;
  return job * 4 + 4;
}
__device__ __forceinline__ int prev_pass(int code) {
  const int job = code >> 2, p = code & 3;
  if (p == 0) return job > 6 ? (job - 1) * 4 : (job - 1) * 4 + 3;
  if (p == 3 && pass_exists(job, 2)) return code - 1;
  if (p >= 2 && pass_exists(job, 1)) return job * 4 + 1;
  return job * 4;
}

__device__ __forceinline__ void proj_pass(const MegaParams& P, uint8_t* sm, uint32_t sbase, int code, int wg) {
  const uint32_t s_bar = sbase + M_BAR;
  const int prev = prev_pass(code);
  if (code > 0) mbar_wait_long(s_bar + B_TURN + (prev & 3) * 8, (prev >> 2) & 1);
  float acc[32];
#pragma unroll
  for (int i = 0; i < 32; i++) acc[i] = 0.f;
  pin(acc);
#pragma unroll
  for (int c = 0; c < 8; c++) {
    const uint32_t st = sbase + M_STAGE + (c & 3) * 16384;
    mbar_wait(s_bar + B_FULL + (c & 3) * 8, c >> 2);
    const uint64_t da = mkdesc(st, 16, 1024, 1), db = mkdesc(st + 8192, 8192, 1024, 1);
    wg_fence();
#pragma unroll
    for (int k = 0; k < 4; k++) wgmma_gemm_n64(acc, da + k * 2, db + k * 128);
    wg_commit();
    if (c & 3) {
      wg_wait<1>();
      if (elect_one()) mbar_arrive(s_bar + B_EMPTY + ((c - 1) & 3) * 8);
    }
    if (c == 3) {
      wg_wait<0>();
      if (elect_one()) mbar_arrive(s_bar + B_EMPTY + 24);
    }
  }
  wg_wait<0>();
  pin(acc);
  if (elect_one()) { mbar_arrive(s_bar + B_EMPTY + 24); mbar_arrive(s_bar + B_TURN + (code & 3) * 8); }
  int t;
  asm volatile("mov.u32 %0, %%tid.x;" : "=r"(t));
  t &= 127;
  const int lane = t & 31, w4 = t >> 5;
  const int l = code >> 3, r = (code >> 2) & 1, p = code & 3;
  const int rb = blockIdx.x >> 3, ct = blockIdx.x & 7, row0 = tok0(r, rb);
  const uint32_t stg = sbase + M_STG;
  if (p == 0) {
    mbar_wait(s_bar + B_RES, r);
    const uint32_t ra = stg + (w4 * 16 + (lane & 15)) * 128;
    float s0 = 0.f, q0 = 0.f, s1 = 0.f, q1 = 0.f;
#pragma unroll
    for (int j = 0; j < 8; j += 2) {
      const uint32_t a = ra + (((j + (lane >> 4)) ^ (lane & 7)) << 4);
      uint32_t y[4];
      ldsm4(a, y[0], y[1], y[2], y[3]);
#pragma unroll
      for (int e = 0; e < 4; e++) {
        y[e] = hadd2_bf16(y[e], pack_bf16(acc[4 * j + 2 * e], acc[4 * j + 2 * e + 1]));
        const float lo = bf_lo(y[e]), hi = bf_hi(y[e]);
        if (e & 1) { s1 += lo + hi; q1 = fmaf(lo, lo, fmaf(hi, hi, q1)); }
        else { s0 += lo + hi; q0 = fmaf(lo, lo, fmaf(hi, hi, q0)); }
      }
      stsm4(a, y[0], y[1], y[2], y[3]);
    }
    __syncwarp();
    __nv_bfloat16* xout = (l == 3 ? P.out : g_x + (size_t)l * S_ * D_) + (size_t)(row0 + w4 * 16 + (lane >> 3)) * D_ + ct * 64 + (lane & 7) * 8;
#pragma unroll
    for (int i = 0; i < 4; i++) {
      const int rr = i * 4 + (lane >> 3);
      *reinterpret_cast<uint4*>(xout + (size_t)i * 4 * D_) = lds128(stg + (w4 * 16 + rr) * 128 + (((lane & 7) ^ (rr & 7)) << 4));
    }
    if (l < 3) {
#pragma unroll
      for (int o = 1; o < 4; o <<= 1) {
        s0 += __shfl_xor_sync(0xffffffffu, s0, o); q0 += __shfl_xor_sync(0xffffffffu, q0, o);
        s1 += __shfl_xor_sync(0xffffffffu, s1, o); q1 += __shfl_xor_sync(0xffffffffu, q1, o);
      }
      if ((lane & 3) == 0) {
        float2* st = g_stats + ((l + 1) * S_ + row0 + w4 * 16 + (lane >> 2)) * 8 + ct;
        st[0] = make_float2(s0, q0); st[64] = make_float2(s1, q1);
      }
      if (r) {
        named_sync(wg + 1, 128);
        if (wu == 0) cnt_signal(CNT_X + (code >> 2) * 16 + rb, 4);
      }
    }
  } else {
    const bool kv = !(l & 1) && p == 1;
    const int type = p == 3 ? 0 : p;
    mbar_wait(s_bar + B_PRE, r);
    mbar_wait(s_bar + B_EPI + (prev & 3) * 8, (prev >> 2) & 1);
    const float2 st0 = reinterpret_cast<const float2*>(sm + M_ROW)[w4 * 16 + (lane >> 2)];
    const float2 st1 = reinterpret_cast<const float2*>(sm + M_ROW)[w4 * 16 + (lane >> 2) + 8];
    const float* cs = reinterpret_cast<const float*>(sm + M_CS) + (p - 1) * 64 + (lane & 3) * 2;
    const uint32_t saddr = stg + (w4 * 16 + (lane & 15)) * STG_PITCH + (lane >> 4) * 16;
    if (kv) {
      proj_stage<true>(acc, 0, saddr, cs, st0.x, st0.y, st1.x, st1.y);
      proj_stage<false>(acc, 2, saddr, cs, st0.x, st0.y, st1.x, st1.y);
    } else if (type == 2) {
#pragma unroll
      for (int j = 0; j < 8; j += 2) proj_stage<false>(acc, j, saddr, cs, st0.x, st0.y, st1.x, st1.y);
    } else {
      const float sc = type == 0 ? QSCALE : 1.f, f0 = st0.y * sc, f1 = st1.y * sc;
#pragma unroll
      for (int j = 0; j < 8; j += 2) proj_stage<true>(acc, j, saddr, cs, st0.x, f0, st1.x, f1);
    }
    named_sync(wg + 1, 128);
    const int row = t & 63;
#pragma unroll
    for (int i = 0; i < 2; i++) {
      if (kv && i == 1) break;
      const int hh = 2 * i + (t >> 6);
      const uint32_t a = stg + row * STG_PITCH + hh * 32;
      const uint32_t ap = row >= 4 ? a - 4 * STG_PITCH : (r ? sbase + M_KTAIL + row * 128 + hh * 32 : 0u);
      proj_store(a, ap, kv ? 1 + hh : type, l + 1, kv ? 0 : ct * 4 + hh, row0 + row);
    }
    if (p == 1 && r == 0 && t < 32)
      *reinterpret_cast<uint4*>(sm + M_KTAIL + t * 16) = lds128(stg + (60 + (t >> 3)) * STG_PITCH + (t & 7) * 16);
  }
  __syncwarp();
  if (lane == 0) mbar_arrive(s_bar + B_EPI + p * 8);
}

__global__ void __launch_bounds__(640, 1) mega_kernel(const __grid_constant__ MegaParams P) {
  extern __shared__ __align__(1024) uint8_t sm[];
  constexpr uint32_t sbase = 1024;
  if (s2u(sm) != sbase) __trap();
  const uint32_t s_bar = sbase + M_BAR;
  const int tid = threadIdx.x, warp = tid >> 5, lane = tid & 31;
  TM(2, 0);
  if (tid == 0) {
    for (int i = 0; i < 4; i++) {
      mbar_init(s_bar + B_FULL + i * 8, 1); mbar_init(s_bar + B_EMPTY + i * 8, 4);
      mbar_init(s_bar + B_TURN + i * 8, 4); mbar_init(s_bar + B_EPI + i * 8, 4);
    }
    for (int i = 0; i < 2; i++) { mbar_init(s_bar + B_KV + i * 8, 1); mbar_init(s_bar + B_Q + i * 8, 1); mbar_init(s_bar + B_ODONE + i * 8, 16); }
    mbar_init(s_bar + B_FREE0, 16);
    mbar_init(s_bar + B_RES, 1);
    mbar_init(s_bar + B_PRE, 1);
    mbar_init(s_bar + B_CHK, 1);
    fence_bar_init();
  }
  if (tid < 512) *reinterpret_cast<uint4*>(sm + M_KV + 16 * 8192 + tid * 16) = make_uint4(0x3f803f80u, 0x3f803f80u, 0x3f803f80u, 0x3f803f80u);
  fence_async_smem();
  __syncthreads();
  const int wg = __shfl_sync(0xffffffffu, warp >> 2, 0);

  if (wg < 4) {
    asm volatile("setmaxnreg.inc.sync.aligned.u32 112;");
    pdl_wait();
    uint32_t pb = POLY_B;
    asm volatile("" : "+r"(pb));
    float s[32], o[12];
    uint32_t p0[16], p1[16];
#pragma unroll
    for (int i = 0; i < 32; i++) s[i] = ((MUFU_MASK >> (i >> 1)) & 1) ? 0.f : EXP_MAGIC;
#pragma unroll
    for (int i = 0; i < 12; i++) o[i] = 0.f;
    uint64_t dq = mkdesc(sbase + M_Q + wg * 2048, 128, 256, 0);
    uint64_t dk0 = mkdesc(sbase + M_KV + k_unit(0, 0) * 8192, 128, 256, 0), dk1 = mkdesc(sbase + M_KV + k_unit(0, 1) * 8192, 128, 256, 0);
    uint64_t dv = mkdesc(sbase + M_KV + v_unit(0, 0) * 8192, 128, 8192, 0);
    int pass_it = -1;
    mbar_wait_long(s_bar + B_Q, 0);
    mbar_wait_long(s_bar + B_KV, 0);
    TM1(3, 3);
    pin(o);
    att_step<false>(s, o, p1, p0, dq, dk0, dv, pb);
    {
#pragma unroll 1
      for (int it = 0; it < 32; it++) {
        const int b = it & 3;
        pin(o);
        att_step<true>(s, o, p0, p1, dq, dk0 + 128, dv, pb);
        att_step<true>(s, o, p1, p0, dq, dk0 + 256, dv + 64, pb);
        att_step<true>(s, o, p0, p1, dq, dk0 + 384, dv + 128, pb);
        att_step<true>(s, o, p1, p0, dq, dk1, dv + 192, pb);
        att_step<true>(s, o, p0, p1, dq, dk1 + 128, dv + 256, pb);
        att_step<true>(s, o, p1, p0, dq, dk1 + 256, dv + 320, pb);
        att_step<true>(s, o, p0, p1, dq, dk1 + 384, dv + 384, pb);
        wg_wait<0>();
        const uint64_t dvp = dv;
        dk0 -= 2048; dk1 -= 1024; dv += (1024ull << 32) - 2048ull;
        if (it == pass_it || b == 3) {
          const int lr = it >> 2, rnd = lr & 1, layer = lr >> 1, par = layer & 1;
          int t;
          asm volatile("mov.u32 %0, %%tid.x;" : "=r"(t));
          const int ln = t & 31, head = blockIdx.x >> 2;
          const int row0 = (blockIdx.x & 3) * 512 + rnd * 256 + wg * 64;
          pin(p1); pin(o);
          wg_fence();
          pv4(o, p1, dvp + 448);
          wg_commit();
          wg_wait<0>();
          pin(o); pin(s);
          if ((it & 7) == 5 && elect_one()) mbar_arrive(s_bar + B_FREE0);
          int code = (lr - 1) * 4 + ((wg - lr + 1) & 3);
          if (b == 3) {
            __nv_bfloat16* dst = g_o + (size_t)(row0 + ((t >> 5) & 3) * 16 + (ln >> 2)) * D_ + head * 16 + (ln & 3) * 2;
            const float l0 = o[8], l1 = o[10];
            float mx = 0.f;
#pragma unroll
            for (int i = 0; i < 8; i++) mx += fabsf(o[i]);
            const float i0 = __fdividef(1.f, l0), i1 = __fdividef(1.f, l1);
            *reinterpret_cast<uint32_t*>(dst) = pack_bf16(o[0] * i0, o[1] * i0);
            *reinterpret_cast<uint32_t*>(dst + 8) = pack_bf16(o[4] * i0, o[5] * i0);
            *reinterpret_cast<uint32_t*>(dst + 8 * D_) = pack_bf16(o[2] * i1, o[3] * i1);
            *reinterpret_cast<uint32_t*>(dst + 8 * D_ + 8) = pack_bf16(o[6] * i1, o[7] * i1);
            mbar_wait(s_bar + B_CHK, par);
            const bool ok = sm[M_CHK + par * 8 + rnd * 4 + wg] && l0 >= 1e-18f && l0 <= 1e37f &&
                            l1 >= 1e-18f && l1 <= 1e37f && mx <= 3e38f;
            uint32_t bad;
            asm volatile("{.reg .pred p, q; setp.eq.u32 p, %1, 0; barrier.red.or.pred.aligned q, %2, 128, p; selp.u32 %0, 1, 0, q;}"
                         : "=r"(bad) : "r"((uint32_t)ok), "r"(wg + 1) : "memory");
            if (bad) {
              att_fallback(P, layer, head, row0, reinterpret_cast<__nv_bfloat16*>(sm + M_Q + rnd * 8192 + wg * 2048), wg + 1);
              fence_async_smem();
              named_sync(wg + 1, 128);
            }
            __syncwarp();
            if (elect_one()) mbar_arrive(s_bar + B_ODONE + rnd * 8);
            if (rnd && __shfl_sync(0xffffffffu, t & 96, 0) == 0) cnt_signal(CNT_O + lr * 16 + (blockIdx.x & 3) * 4 + wg, 4);
#pragma unroll
            for (int i = 0; i < 32; i++) s[i] = ((MUFU_MASK >> (i >> 1)) & 1) ? 0.f : EXP_MAGIC;
#pragma unroll
            for (int i = 0; i < 12; i++) o[i] = 0.f;
            const int pp = (wg - lr) & 3;
            code = pp == 0 ? lr * 4 : -1;
            pass_it = pp > 0 && pass_exists(lr, pp) ? it + ((rnd || pp == 1) ? 2 : 3) : -1;
            dq += rnd ? -512ll : 512ll;
            dk0 += 4 * 2048; dk1 += 4 * 1024; dv -= (4096ull << 32) - 4 * 2048ull;
          }
          if (code >= 0) {
            TM3(24 + code, 0);
            proj_pass(P, sm, sbase, code, wg);
            TM3(24 + code, 1);
          }
          if (it == 31) break;
          if (b & 1) {
            if (HOLD && (it & 7) == 7 && ((wg - lr) & 3) <= HOLD) mbar_wait_long(s_bar + B_TURN, 1);
          if (b == 3) mbar_wait_long(s_bar + B_Q + (~it & 4) * 2, ((it + 1) >> 3) & 1);
            mbar_wait_long(s_bar + B_KV + (~b & 2) * 4, ((it + 1) >> 3) & 1);
            if (b == 3) TM1(3 + ((it + 1) >> 2), 3);
          }
          pin(o);
          att_step<false>(s, o, p1, p0, dq, dk0, dv, pb);
        } else {
          if (b == 1) {
            TM1(3 + (it >> 2), 4);
            mbar_wait_long(s_bar + B_KV + 8, (it >> 3) & 1);
            TM1(3 + (it >> 2), 5);
          }
          att_step<true>(s, o, p1, p0, dq, dk0, dvp + 448, pb);
          wg_wait<0>();
          if ((it & 7) == 5 && elect_one()) mbar_arrive(s_bar + B_FREE0);
        }
      }
    }
  } else {
    asm volatile("setmaxnreg.dec.sync.aligned.u32 32;");
    const int w4 = __shfl_sync(0xffffffffu, warp & 3, 0);
    const int rb = blockIdx.x >> 3, ct = blockIdx.x & 7;
    if (EXP_NIT < 32 && EXP_AUX == 0) {
      if (w4 == 2) { pdl_wait(); load_q(sbase, 0, 0); load_kv(sbase, 0, 0); load_kv(sbase, 0, 1); load_q(sbase, 0, 1); }
    } else if (EXP_NIT < 32) {
      if (w4 == 2) { pdl_wait(); load_q(sbase, 0, 0); load_kv(sbase, 0, 0); load_kv(sbase, 0, 1); load_q(sbase, 0, 1); }
      mbar_wait_long(s_bar + B_ODONE + 8, 0);
    } else if (w4 == 0) {
      int code = 0;
      bool gated = true;
#pragma unroll 1
      while (code < 32) {
        code = __shfl_sync(0xffffffffu, code, 0);
        const int job = code >> 2, p = code & 3;
        const CUtensorMap* mb = b_map(P, code);
        const CUtensorMap* ma = &P.m[p == 0 ? 1 : 0];
        const int colb = b_col(code), rowa = tok0(job & 1, rb) + (p == 0 ? 0 : (code >> 3) * S_);
#pragma unroll 1
        for (int c = 0; c < 4; c++) {
          if (code > 0) mbar_wait(s_bar + B_EMPTY + c * 8, 1);
          if (elect_one()) {
            issue_b(sbase, mb, colb, c, c);
            if (!gated) issue_a(sbase, ma, rowa, c, c);
          }
        }
        if (gated) {
          if (p == 0) {
            if (code == 0) pdl_wait();
            else { const int prev = prev_pass(code); mbar_wait_long(s_bar + B_EPI + (prev & 3) * 8, (prev >> 2) & 1); }
            if (elect_one()) {
              asm volatile("fence.proxy.async;" ::: "memory");
              mbar_expect(s_bar + B_RES, 8192);
              tma_load(sbase + M_STG, &P.m[job < 2 ? 7 : 0], ct * 64, tok0(job & 1, rb) + (job < 2 ? 0 : ((job >> 1) - 1) * S_), s_bar + B_RES);
            }
            mbar_wait_long(s_bar + B_ODONE + (job & 1) * 8, (job >> 1) & 1);
            cnt_wait(CNT_O + job * 16 + rb, 128);
            TM2(12 + job, 1);
          } else {
            mbar_wait_long(s_bar + B_EPI, job & 1);
            cnt_wait(CNT_X + job * 16 + rb, 32);
            TM2(12 + job, 3);
          }
          if (elect_one()) {
#pragma unroll
            for (int c = 0; c < 4; c++) issue_a(sbase, ma, rowa, c, c);
          }
        }
#pragma unroll 1
        for (int c = 0; c < 4; c++) {
          mbar_wait(s_bar + B_EMPTY + c * 8, 0);
          if (elect_one()) {
            issue_b(sbase, mb, colb, c, c + 4);
            issue_a(sbase, ma, rowa, c, c + 4);
          }
        }
        code = next_pass(code);
        gated = p == 0 || (code & 3) == 0;
      }
    } else if (w4 == 1) {
#pragma unroll 1
      for (int job = 0; job < 8; job++) {
        mbar_wait_long(s_bar + B_ODONE + (job & 1) * 8, (job >> 1) & 1);
        if (!(job & 1)) {
          asm volatile("fence.acq_rel.gpu;" ::: "memory");
          if (lane < 4) asm volatile("red.relaxed.gpu.global.add.u32 [%0], 4;" ::"l"(g_cnt + CNT_O + job * 16 + (blockIdx.x & 3) * 4 + lane) : "memory");
        }
        if (job >= 6) continue;
        mbar_wait_long(s_bar + B_EPI, job & 1);
        if (!(job & 1)) cnt_signal(CNT_X + job * 16 + rb, 4);
        if (pass_exists(job, 1)) {
          mbar_wait_long(s_bar + B_EPI + 8, job & 1);
          if (job & 2) mbar_wait_long(s_bar + B_EPI + 16, job & 1);
          cnt_signal(CNT_KV + job * 8 + ct);
        }
        mbar_wait_long(s_bar + B_EPI + 24, job & 1);
        cnt_signal(CNT_Q + (job * 4 + (rb >> 2)) * 8 + ct);
      }
    } else if (w4 == 2) {
      pdl_wait();
      load_q(sbase, 0, 0); load_kv(sbase, 0, 0); load_kv(sbase, 0, 1); load_q(sbase, 0, 1);
#pragma unroll 1
      for (int job = 0; job < 6; job++) {
        const int l = job >> 1, r = job & 1;
        mbar_wait_long(s_bar + B_ODONE + r * 8, l & 1);
        if (r == 0) mbar_wait_long(s_bar + B_FREE0, l & 1);
        mbar_wait_long(s_bar + B_TURN, job & 1);
        cnt_wait(CNT_KV + job * 8 + ((l & 1) ? blockIdx.x >> 4 : 0), 16);
        load_kv(sbase, l + 1, r);
        cnt_wait(CNT_Q + (job * 4 + (blockIdx.x & 3)) * 8 + (blockIdx.x >> 4), 4);
        load_q(sbase, l + 1, r);
      }
    } else {
      pdl_wait();
#pragma unroll 1
      for (int job = -1; job < 6; job++) {
        if (job & 1) {
          const int l = (job + 1) >> 1, head = blockIdx.x >> 2;
          if (job > 0) { mbar_wait_long(s_bar + B_KV + 8, l & 1); mbar_wait_long(s_bar + B_Q + 8, l & 1); }
          const float* nk = g_nrm + ((l * 2 + 1) * H_ + ((l & 1) ? 0 : head)) * 64;
          const unsigned q = __float_as_uint(__ldcg(g_nrm + (l * 2 * H_ + head) * 64 + (blockIdx.x & 3) * 16 + (lane & 15)));
          const unsigned kn = __reduce_max_sync(0xffffffffu, max(__float_as_uint(__ldcg(nk + lane)), __float_as_uint(__ldcg(nk + 32 + lane))));
          const unsigned qn = max(q, __shfl_xor_sync(0xffffffffu, q, 1));
          if (lane < 16 && !(lane & 1))
            sm[M_CHK + (l & 1) * 8 + (lane >> 1)] = __uint_as_float(qn) * __uint_as_float(kn) <= SCORE_LIMIT * SCORE_LIMIT;
          __syncwarp();
          if (elect_one()) mbar_arrive(s_bar + B_CHK);
        }
        if (job == 5) break;
        job++;
        float c[6];
#pragma unroll
        for (int i = 0; i < 6; i++) {
          const int p = 1 + (i >> 1);
          c[i] = __ldcg(g_colsum + ((job & 2) ? (p == 3 ? 0 : p * 512) + ct * 64 : (p == 3 ? 1536 + ct * 64 : 2048)) + (i & 1) * 32 + lane);
        }
        mbar_wait_long(s_bar + B_TURN, job & 1);
#pragma unroll
        for (int i = 0; i < 6; i++) reinterpret_cast<float*>(sm + M_CS)[i * 32 + lane] = c[i];
        __syncwarp();
        if (elect_one()) mbar_arrive(s_bar + B_PRE);
        job--;
      }
    }
    named_sync(5, 128);
    if (tid == 512) {
      unsigned old;
      asm volatile("atom.acq_rel.gpu.global.add.u32 %0, [%1], 1;" : "=r"(old) : "l"(g_cnt + CNT_DONE) : "memory");
      if (old == gridDim.x - 1)
        for (int i = 0; i < CNT_N; i++) g_cnt[i] = 0u;
    }
  }
}

typedef CUresult (*EncodeFn)(CUtensorMap*, CUtensorMapDataType, cuuint32_t, void*, const cuuint64_t*, const cuuint64_t*,
                             const cuuint32_t*, const cuuint32_t*, CUtensorMapInterleave, CUtensorMapSwizzle,
                             CUtensorMapL2promotion, CUtensorMapFloatOOBfill);

void make_map(EncodeFn enc, CUtensorMap* m, const void* p, int rows, int cols) {
  cuuint64_t dim[2] = {(cuuint64_t)cols, (cuuint64_t)rows};
  cuuint64_t str[1] = {(cuuint64_t)cols * 2};
  cuuint32_t box[2] = {64, 64};
  cuuint32_t es[2] = {1, 1};
  enc(m, CU_TENSOR_MAP_DATA_TYPE_BFLOAT16, 2, const_cast<void*>(p), dim, str, box, es, CU_TENSOR_MAP_INTERLEAVE_NONE,
      CU_TENSOR_MAP_SWIZZLE_128B, CU_TENSOR_MAP_L2_PROMOTION_L2_128B, CU_TENSOR_MAP_FLOAT_OOB_FILL_NONE);
}

template <typename... KA, typename... A>
void launch(void (*k)(KA...), int grid, int block, int smem, bool pdl, A... args) {
  cudaLaunchConfig_t cfg = {};
  cfg.gridDim = dim3(grid); cfg.blockDim = dim3(block); cfg.dynamicSmemBytes = smem; cfg.stream = cudaStreamPerThread;
  cudaLaunchAttribute at[1];
  at[0].id = cudaLaunchAttributeProgrammaticStreamSerialization;
  at[0].val.programmaticStreamSerializationAllowed = 1;
  cfg.attrs = at; cfg.numAttrs = pdl ? 1 : 0;
  cudaLaunchKernelEx(&cfg, k, KA(args)...);
}

struct HostState {
  bool init;
  const void* in[8];
  MegaParams mp;
};
HostState hs;

}

extern "C" void kernel_launch(void* const* d_in, const int* in_sizes, int n_in, void* d_out, int out_size) {
  const __nv_bfloat16* A_x = (const __nv_bfloat16*)d_in[0];
  const __nv_bfloat16* A_wqkv = (const __nv_bfloat16*)d_in[1];
  const __nv_bfloat16* A_wo = (const __nv_bfloat16*)d_in[2];
  const __nv_bfloat16* B_wq = (const __nv_bfloat16*)d_in[4];
  const __nv_bfloat16* B_wk = (const __nv_bfloat16*)d_in[5];
  const __nv_bfloat16* B_wv = (const __nv_bfloat16*)d_in[6];
  const __nv_bfloat16* B_wo = (const __nv_bfloat16*)d_in[7];
  bool same = hs.init;
  for (int i = 0; i < 8; i++) same = same && hs.in[i] == d_in[i];
  if (!same) {
    void* fn = nullptr;
    cudaDriverEntryPointQueryResult qr;
    cudaGetDriverEntryPoint("cuTensorMapEncodeTiled", &fn, cudaEnableDefault, &qr);
    EncodeFn enc = (EncodeFn)fn;
    void *px, *po, *pw;
    cudaGetSymbolAddress(&px, g_x);
    cudaGetSymbolAddress(&po, g_o);
    cudaGetSymbolAddress(&pw, g_wkv);
    make_map(enc, &hs.mp.m[7], A_x, S_, D_);
    make_map(enc, &hs.mp.m[0], px, 3 * S_, D_);
    make_map(enc, &hs.mp.m[1], po, S_, D_);
    make_map(enc, &hs.mp.m[2], A_wqkv, D_, 1536);
    make_map(enc, &hs.mp.m[3], B_wq, D_, 512);
    make_map(enc, &hs.mp.m[4], pw, D_, 32);
    make_map(enc, &hs.mp.m[5], A_wo, D_, D_);
    make_map(enc, &hs.mp.m[6], B_wo, D_, D_);
    hs.mp.x0 = A_x; hs.mp.wqkv = A_wqkv; hs.mp.wq = B_wq; hs.mp.wk = B_wk;
    cudaFuncSetAttribute(prep_kernel, cudaFuncAttributePreferredSharedMemoryCarveout, 100);
    cudaFuncSetAttribute(g1a_kernel, cudaFuncAttributeMaxDynamicSharedMemorySize, G1A_SMEM);
    cudaFuncSetAttribute(mega_kernel, cudaFuncAttributeMaxDynamicSharedMemorySize, MEGA_SMEM);
    for (int i = 0; i < 8; i++) hs.in[i] = d_in[i];
    hs.init = true;
  }
  hs.mp.out = (__nv_bfloat16*)d_out;
  launch(prep_kernel, 130, 256, 0, false, A_x, A_wqkv, B_wq, B_wk, B_wv);
  launch(g1a_kernel, 128, 288, G1A_SMEM, true, hs.mp.m[7], hs.mp.m[2]);
  launch(mega_kernel, 128, 640, MEGA_SMEM, true, hs.mp);
}
```

```cpp
#include <cuda_runtime.h>
#include <cuda_bf16.h>
#include <cuda_fp16.h>
#include <cuda.h>
#include <stdint.h>

namespace {

constexpr int S_ = 2048, D_ = 512, H_ = 32;

__device__ __align__(1024) __nv_bfloat16 g_x[3 * S_ * D_];
__device__ __align__(1024) __nv_bfloat16 g_o[S_ * D_];
__device__ __align__(1024) uint4 g_q[2 * H_ * S_ * 2];
__device__ __align__(1024) uint4 g_k[2 * H_ * S_ * 2];
__device__ __align__(1024) uint4 g_v[2 * H_ * S_ * 2];
__device__ __align__(1024) __nv_bfloat16 g_wkv[D_ * 32];
__device__ __align__(16) float2 g_stats[4 * S_ * 8];
__device__ __align__(16) float g_colsum[1536 + 512 + 32];
__device__ float g_nk[4 * H_ * 64];
__device__ float g_nq[4 * 8 * 128];
constexpr int CNT_O = 0, CNT_X = 128, CNT_KV = CNT_X + 128, CNT_Q = CNT_KV + 64, CNT_PREP = CNT_Q + 256, CNT_DONE = CNT_PREP + 1,
              CNT_N = CNT_DONE + 1;
#define CNT_STRIDE 32
__device__ __align__(1024) unsigned g_cnt[CNT_N * CNT_STRIDE];

#define TM(k, slot)
#define TM1(k, slot)
#define TM2(k, slot)
#define TSM(k)
#define TM3(k, slot)
__device__ __forceinline__ uint32_t s2u(const void* p) { return (uint32_t)__cvta_generic_to_shared(p); }
__device__ __forceinline__ void mbar_init(uint32_t bar, int cnt) {
  asm volatile("mbarrier.init.shared::cta.b64 [%0], %1;" ::"r"(bar), "r"(cnt) : "memory");
}
__device__ __forceinline__ void mbar_expect(uint32_t bar, uint32_t bytes) {
  asm volatile("mbarrier.arrive.expect_tx.shared::cta.b64 _, [%0], %1;" ::"r"(bar), "r"(bytes) : "memory");
}
__device__ __forceinline__ void mbar_arrive(uint32_t bar) {
  asm volatile("mbarrier.arrive.shared::cta.b64 _, [%0];" ::"r"(bar) : "memory");
}
__device__ __forceinline__ bool mbar_try(uint32_t bar, uint32_t par) {
  uint32_t ok;
  asm volatile("{.reg .pred p; mbarrier.try_wait.parity.shared::cta.b64 p, [%1], %2; selp.u32 %0,1,0,p;}"
               : "=r"(ok) : "r"(bar), "r"(par) : "memory");
  return ok;
}
__device__ __forceinline__ uint32_t clock32() { uint32_t c; asm volatile("mov.u32 %0, %%clock;" : "=r"(c)); return c; }
#define GIVE_UP(v_) __trap()
constexpr uint32_t WAIT_LIMIT = 2000000000u;
__device__ __forceinline__ void mbar_wait(uint32_t bar, uint32_t par) {
  if (mbar_try(bar, par)) return;
  const uint32_t t0 = clock32();
  while (!mbar_try(bar, par))
    if (clock32() - t0 > WAIT_LIMIT) GIVE_UP(bar * 2 + par);
}
#define SLEEP_NS 32
__device__ __forceinline__ bool mbar_test(uint32_t bar, uint32_t par) {
  uint32_t ok;
  asm volatile("{.reg .pred p; mbarrier.test_wait.parity.shared::cta.b64 p, [%1], %2; selp.u32 %0,1,0,p;}"
               : "=r"(ok) : "r"(bar), "r"(par) : "memory");
  return ok;
}
#define WAITMODE 2
__device__ __forceinline__ void mbar_wait_long(uint32_t bar, uint32_t par) {
  if (mbar_test(bar, par)) return;
  const uint32_t t0 = clock32();
  if (WAITMODE == 0) {
    do {
      if (clock32() - t0 > WAIT_LIMIT) GIVE_UP(bar * 2 + par);
      __nanosleep(SLEEP_NS);
    } while (!mbar_test(bar, par));
  } else if (WAITMODE == 1) {
    uint32_t ok;
    do {
      if (clock32() - t0 > WAIT_LIMIT) GIVE_UP(bar * 2 + par);
      asm volatile("{.reg .pred p; mbarrier.try_wait.parity.shared::cta.b64 p, [%1], %2, 10000; selp.u32 %0,1,0,p;}"
                   : "=r"(ok) : "r"(bar), "r"(par) : "memory");
    } while (!ok);
  } else {
    while (!mbar_try(bar, par))
      if (clock32() - t0 > WAIT_LIMIT) GIVE_UP(bar * 2 + par);
  }
}
__device__ __forceinline__ void bulk_load(uint32_t dst, const void* src, uint32_t bytes, uint32_t bar) {
  asm volatile("cp.async.bulk.shared::cluster.global.mbarrier::complete_tx::bytes [%0], [%1], %2, [%3];"
               ::"r"(dst), "l"(src), "r"(bytes), "r"(bar) : "memory");
}
__device__ __forceinline__ void tma_load(uint32_t dst, const CUtensorMap* m, int c0, int c1, uint32_t bar) {
  asm volatile("cp.async.bulk.tensor.2d.shared::cluster.global.mbarrier::complete_tx::bytes [%0], [%1, {%3, %4}], [%2];"
               ::"r"(dst), "l"(m), "r"(bar), "r"(c0), "r"(c1) : "memory");
}
__device__ __forceinline__ void tma_store(const CUtensorMap* m, int c0, int c1, uint32_t src) {
  asm volatile("cp.async.bulk.tensor.2d.global.shared::cta.bulk_group [%0, {%2, %3}], [%1];" ::"l"(m), "r"(src), "r"(c0), "r"(c1) : "memory");
}
__device__ __forceinline__ void tma_store4(const CUtensorMap* m, int c0, int c1, int c2, int c3, uint32_t src) {
  asm volatile("cp.async.bulk.tensor.4d.global.shared::cta.bulk_group [%0, {%2, %3, %4, %5}], [%1];"
               ::"l"(m), "r"(src), "r"(c0), "r"(c1), "r"(c2), "r"(c3) : "memory");
}
__device__ __forceinline__ void bulk_store(void* dst, uint32_t src, uint32_t bytes) {
  asm volatile("cp.async.bulk.global.shared::cta.bulk_group [%0], [%1], %2;" ::"l"(dst), "r"(src), "r"(bytes) : "memory");
}
__device__ __forceinline__ bool elect_one() {
  uint32_t p;
  asm volatile("{.reg .pred q; elect.sync _|q, 0xffffffff; selp.u32 %0, 1, 0, q;}" : "=r"(p));
  return p;
}
__device__ __forceinline__ void pdl_wait() { asm volatile("griddepcontrol.wait;" ::: "memory"); }
__device__ __forceinline__ void pdl_launch() { asm volatile("griddepcontrol.launch_dependents;" ::: "memory"); }
__device__ __forceinline__ void fence_async_smem() { asm volatile("fence.proxy.async.shared::cta;" ::: "memory"); }
__device__ __forceinline__ void fence_bar_init() { asm volatile("fence.mbarrier_init.release.cluster;" ::: "memory"); }
__device__ __forceinline__ void named_sync(int id, int n) { asm volatile("bar.sync %0, %1;" ::"r"(id), "r"(n) : "memory"); }
__device__ __forceinline__ void wg_fence() { asm volatile("wgmma.fence.sync.aligned;" ::: "memory"); }
__device__ __forceinline__ void wg_commit() { asm volatile("wgmma.commit_group.sync.aligned;" ::: "memory"); }
template <int N> __device__ __forceinline__ void wg_wait() { asm volatile("wgmma.wait_group.sync.aligned %0;" ::"n"(N) : "memory"); }
template <int N> __device__ __forceinline__ void pin(float (&d)[N]) {
#pragma unroll
  for (int i = 0; i < N; i++) asm volatile("" : "+f"(d[i])::"memory");
}
template <int N> __device__ __forceinline__ void pin(uint32_t (&d)[N]) {
#pragma unroll
  for (int i = 0; i < N; i++) asm volatile("" : "+r"(d[i])::"memory");
}
__device__ __forceinline__ uint64_t mkdesc(uint32_t addr, uint32_t lbo, uint32_t sbo, uint64_t swz) {
  return (uint64_t)((addr & 0x3FFFF) >> 4) | ((uint64_t)(lbo >> 4) << 16) | ((uint64_t)(sbo >> 4) << 32) | (swz << 62);
}
__device__ __forceinline__ uint32_t pack_bf16(float lo, float hi) {
  uint32_t d; asm("cvt.rn.bf16x2.f32 %0, %1, %2;" : "=r"(d) : "f"(hi), "f"(lo)); return d;
}
__device__ __forceinline__ uint32_t pack_f16(float lo, float hi) {
  uint32_t d; asm("cvt.rn.f16x2.f32 %0, %1, %2;" : "=r"(d) : "f"(hi), "f"(lo)); return d;
}
__device__ __forceinline__ float bf_lo(uint32_t v) { return __uint_as_float(v << 16); }
__device__ __forceinline__ float bf_hi(uint32_t v) { return __uint_as_float(v & 0xffff0000u); }
__device__ __forceinline__ void stsm4(uint32_t addr, uint32_t a, uint32_t b, uint32_t c, uint32_t d) {
  asm volatile("stmatrix.sync.aligned.m8n8.x4.shared.b16 [%0], {%1,%2,%3,%4};" ::"r"(addr), "r"(a), "r"(b), "r"(c), "r"(d) : "memory");
}
__device__ __forceinline__ void ldsm4(uint32_t addr, uint32_t& a, uint32_t& b, uint32_t& c, uint32_t& d) {
  asm volatile("ldmatrix.sync.aligned.m8n8.x4.shared.b16 {%0,%1,%2,%3}, [%4];" : "=r"(a), "=r"(b), "=r"(c), "=r"(d) : "r"(addr) : "memory");
}
__device__ __forceinline__ uint32_t hadd2_bf16(uint32_t a, uint32_t b) {
  uint32_t d; asm("add.rn.bf16x2 %0, %1, %2;" : "=r"(d) : "r"(a), "r"(b)); return d;
}
__device__ __forceinline__ uint4 lds128(uint32_t addr) {
  uint4 v; asm volatile("ld.shared.v4.u32 {%0,%1,%2,%3}, [%4];" : "=r"(v.x), "=r"(v.y), "=r"(v.z), "=r"(v.w) : "r"(addr) : "memory"); return v;
}

__device__ __forceinline__ void wgmma_qk_n64(float (&d)[32], uint64_t da, uint64_t db) {
  asm volatile("wgmma.mma_async.sync.aligned.m64n64k16.f32.f16.f16 "
      "{%0,%1,%2,%3,%4,%5,%6,%7,%8,%9,%10,%11,%12,%13,%14,%15,%16,%17,%18,%19,%20,%21,%22,%23,%24,%25,%26,%27,%28,%29,%30,%31}, "
      "%32, %33, 1, 1, 1, 0, 0;"
    : "+f"(d[0]), "+f"(d[1]), "+f"(d[2]), "+f"(d[3]), "+f"(d[4]), "+f"(d[5]), "+f"(d[6]), "+f"(d[7]), "+f"(d[8]),
      "+f"(d[9]), "+f"(d[10]), "+f"(d[11]), "+f"(d[12]), "+f"(d[13]), "+f"(d[14]), "+f"(d[15]), "+f"(d[16]),
      "+f"(d[17]), "+f"(d[18]), "+f"(d[19]), "+f"(d[20]), "+f"(d[21]), "+f"(d[22]), "+f"(d[23]), "+f"(d[24]),
      "+f"(d[25]), "+f"(d[26]), "+f"(d[27]), "+f"(d[28]), "+f"(d[29]), "+f"(d[30]), "+f"(d[31])
    : "l"(da), "l"(db));
}
__device__ __forceinline__ void wgmma_pv_n24(float (&d)[12], uint32_t a0, uint32_t a1, uint32_t a2, uint32_t a3, uint64_t db) {
  asm volatile("wgmma.mma_async.sync.aligned.m64n24k16.f32.bf16.bf16 "
      "{%0,%1,%2,%3,%4,%5,%6,%7,%8,%9,%10,%11}, "
      "{%12,%13,%14,%15}, %16, 1, 1, 1, 1;"
    : "+f"(d[0]), "+f"(d[1]), "+f"(d[2]), "+f"(d[3]), "+f"(d[4]), "+f"(d[5]), "+f"(d[6]), "+f"(d[7]), "+f"(d[8]),
      "+f"(d[9]), "+f"(d[10]), "+f"(d[11])
    : "r"(a0), "r"(a1), "r"(a2), "r"(a3), "l"(db));
}
__device__ __forceinline__ void wgmma_gemm_n64(float (&d)[32], uint64_t da, uint64_t db) {
  asm volatile("wgmma.mma_async.sync.aligned.m64n64k16.f32.bf16.bf16 "
      "{%0,%1,%2,%3,%4,%5,%6,%7,%8,%9,%10,%11,%12,%13,%14,%15,%16,%17,%18,%19,%20,%21,%22,%23,%24,%25,%26,%27,%28,%29,%30,%31}, "
      "%32, %33, 1, 1, 1, 0, 1;"
    : "+f"(d[0]), "+f"(d[1]), "+f"(d[2]), "+f"(d[3]), "+f"(d[4]), "+f"(d[5]), "+f"(d[6]), "+f"(d[7]), "+f"(d[8]),
      "+f"(d[9]), "+f"(d[10]), "+f"(d[11]), "+f"(d[12]), "+f"(d[13]), "+f"(d[14]), "+f"(d[15]), "+f"(d[16]),
      "+f"(d[17]), "+f"(d[18]), "+f"(d[19]), "+f"(d[20]), "+f"(d[21]), "+f"(d[22]), "+f"(d[23]), "+f"(d[24]),
      "+f"(d[25]), "+f"(d[26]), "+f"(d[27]), "+f"(d[28]), "+f"(d[29]), "+f"(d[30]), "+f"(d[31])
    : "l"(da), "l"(db));
}
__device__ __forceinline__ void wgmma_gemm_n64_first(float (&d)[32], uint64_t da, uint64_t db) {
  asm volatile("wgmma.mma_async.sync.aligned.m64n64k16.f32.bf16.bf16 "
      "{%0,%1,%2,%3,%4,%5,%6,%7,%8,%9,%10,%11,%12,%13,%14,%15,%16,%17,%18,%19,%20,%21,%22,%23,%24,%25,%26,%27,%28,%29,%30,%31}, "
      "%32, %33, 0, 1, 1, 0, 1;"
    : "=f"(d[0]), "=f"(d[1]), "=f"(d[2]), "=f"(d[3]), "=f"(d[4]), "=f"(d[5]), "=f"(d[6]), "=f"(d[7]), "=f"(d[8]),
      "=f"(d[9]), "=f"(d[10]), "=f"(d[11]), "=f"(d[12]), "=f"(d[13]), "=f"(d[14]), "=f"(d[15]), "=f"(d[16]),
      "=f"(d[17]), "=f"(d[18]), "=f"(d[19]), "=f"(d[20]), "=f"(d[21]), "=f"(d[22]), "=f"(d[23]), "=f"(d[24]),
      "=f"(d[25]), "=f"(d[26]), "=f"(d[27]), "=f"(d[28]), "=f"(d[29]), "=f"(d[30]), "=f"(d[31])
    : "l"(da), "l"(db));
}
__device__ __forceinline__ void wgmma_gemm_n32(float (&d)[16], uint64_t da, uint64_t db) {
  asm volatile("wgmma.mma_async.sync.aligned.m64n32k16.f32.bf16.bf16 "
      "{%0,%1,%2,%3,%4,%5,%6,%7,%8,%9,%10,%11,%12,%13,%14,%15}, "
      "%16, %17, 1, 1, 1, 0, 1;"
    : "+f"(d[0]), "+f"(d[1]), "+f"(d[2]), "+f"(d[3]), "+f"(d[4]), "+f"(d[5]), "+f"(d[6]), "+f"(d[7]), "+f"(d[8]),
      "+f"(d[9]), "+f"(d[10]), "+f"(d[11]), "+f"(d[12]), "+f"(d[13]), "+f"(d[14]), "+f"(d[15])
    : "l"(da), "l"(db));
}
__device__ __forceinline__ void wgmma_gemm_n128(float (&d0)[32], float (&d1)[32], uint64_t da, uint64_t db) {
  asm volatile("wgmma.mma_async.sync.aligned.m64n128k16.f32.bf16.bf16 "
      "{%0,%1,%2,%3,%4,%5,%6,%7,%8,%9,%10,%11,%12,%13,%14,%15,%16,%17,%18,%19,%20,%21,%22,%23,%24,%25,%26,%27,%28,%29,%30,%31,%32,%33,%34,%35,%36,%37,%38,%39,%40,%41,%42,%43,%44,%45,%46,%47,%48,%49,%50,%51,%52,%53,%54,%55,%56,%57,%58,%59,%60,%61,%62,%63}, "
      "%64, %65, 1, 1, 1, 0, 1;"
    : "+f"(d0[0]), "+f"(d0[1]), "+f"(d0[2]), "+f"(d0[3]), "+f"(d0[4]), "+f"(d0[5]), "+f"(d0[6]), "+f"(d0[7]),
      "+f"(d0[8]), "+f"(d0[9]), "+f"(d0[10]), "+f"(d0[11]), "+f"(d0[12]), "+f"(d0[13]), "+f"(d0[14]), "+f"(d0[15]),
      "+f"(d0[16]), "+f"(d0[17]), "+f"(d0[18]), "+f"(d0[19]), "+f"(d0[20]), "+f"(d0[21]), "+f"(d0[22]), "+f"(d0[23]),
      "+f"(d0[24]), "+f"(d0[25]), "+f"(d0[26]), "+f"(d0[27]), "+f"(d0[28]), "+f"(d0[29]), "+f"(d0[30]), "+f"(d0[31]),
      "+f"(d1[0]), "+f"(d1[1]), "+f"(d1[2]), "+f"(d1[3]), "+f"(d1[4]), "+f"(d1[5]), "+f"(d1[6]), "+f"(d1[7]),
      "+f"(d1[8]), "+f"(d1[9]), "+f"(d1[10]), "+f"(d1[11]), "+f"(d1[12]), "+f"(d1[13]), "+f"(d1[14]), "+f"(d1[15]),
      "+f"(d1[16]), "+f"(d1[17]), "+f"(d1[18]), "+f"(d1[19]), "+f"(d1[20]), "+f"(d1[21]), "+f"(d1[22]), "+f"(d1[23]),
      "+f"(d1[24]), "+f"(d1[25]), "+f"(d1[26]), "+f"(d1[27]), "+f"(d1[28]), "+f"(d1[29]), "+f"(d1[30]), "+f"(d1[31])
    : "l"(da), "l"(db));
}
__device__ __forceinline__ void wgmma_gemm_n128_first(float (&d0)[32], float (&d1)[32], uint64_t da, uint64_t db) {
  asm volatile("wgmma.mma_async.sync.aligned.m64n128k16.f32.bf16.bf16 "
      "{%0,%1,%2,%3,%4,%5,%6,%7,%8,%9,%10,%11,%12,%13,%14,%15,%16,%17,%18,%19,%20,%21,%22,%23,%24,%25,%26,%27,%28,%29,%30,%31,%32,%33,%34,%35,%36,%37,%38,%39,%40,%41,%42,%43,%44,%45,%46,%47,%48,%49,%50,%51,%52,%53,%54,%55,%56,%57,%58,%59,%60,%61,%62,%63}, "
      "%64, %65, 0, 1, 1, 0, 1;"
    : "=f"(d0[0]), "=f"(d0[1]), "=f"(d0[2]), "=f"(d0[3]), "=f"(d0[4]), "=f"(d0[5]), "=f"(d0[6]), "=f"(d0[7]),
      "=f"(d0[8]), "=f"(d0[9]), "=f"(d0[10]), "=f"(d0[11]), "=f"(d0[12]), "=f"(d0[13]), "=f"(d0[14]), "=f"(d0[15]),
      "=f"(d0[16]), "=f"(d0[17]), "=f"(d0[18]), "=f"(d0[19]), "=f"(d0[20]), "=f"(d0[21]), "=f"(d0[22]), "=f"(d0[23]),
      "=f"(d0[24]), "=f"(d0[25]), "=f"(d0[26]), "=f"(d0[27]), "=f"(d0[28]), "=f"(d0[29]), "=f"(d0[30]), "=f"(d0[31]),
      "=f"(d1[0]), "=f"(d1[1]), "=f"(d1[2]), "=f"(d1[3]), "=f"(d1[4]), "=f"(d1[5]), "=f"(d1[6]), "=f"(d1[7]),
      "=f"(d1[8]), "=f"(d1[9]), "=f"(d1[10]), "=f"(d1[11]), "=f"(d1[12]), "=f"(d1[13]), "=f"(d1[14]), "=f"(d1[15]),
      "=f"(d1[16]), "=f"(d1[17]), "=f"(d1[18]), "=f"(d1[19]), "=f"(d1[20]), "=f"(d1[21]), "=f"(d1[22]), "=f"(d1[23]),
      "=f"(d1[24]), "=f"(d1[25]), "=f"(d1[26]), "=f"(d1[27]), "=f"(d1[28]), "=f"(d1[29]), "=f"(d1[30]), "=f"(d1[31])
    : "l"(da), "l"(db));
}

constexpr float QSCALE = 0.25f * 1.4426950408889634f;
constexpr float LN_EPS = 1e-5f;

__device__ __forceinline__ void row_stats(int layer, int row, float& mu, float& rstd) {
  const float4* p = reinterpret_cast<const float4*>(g_stats + (layer * S_ + row) * 8);
  float4 a = __ldcg(p), b = __ldcg(p + 1), c = __ldcg(p + 2), d = __ldcg(p + 3);
  float s = (a.x + a.z) + (b.x + b.z) + (c.x + c.z) + (d.x + d.z);
  float q = (a.y + a.w) + (b.y + b.w) + (c.y + c.w) + (d.y + d.w);
  mu = s * (1.f / D_);
  float var = fmaxf(q * (1.f / D_) - mu * mu, 0.f);
  rstd = rsqrtf(var + LN_EPS);
}

#define PF 0
__global__ void __launch_bounds__(256) prep_kernel(const __nv_bfloat16* __restrict__ x, const __nv_bfloat16* __restrict__ wqkv,
                                                   const __nv_bfloat16* __restrict__ wq, const __nv_bfloat16* __restrict__ wk,
                                                   const __nv_bfloat16* __restrict__ wv, const __nv_bfloat16* woa, const __nv_bfloat16* wob) {
  TM(0, 0);
  pdl_launch();
  if (PF && blockIdx.x < 128 && threadIdx.x == 0) {
    asm volatile("cp.async.bulk.prefetch.L2.global [%0], 12288;" ::"l"(wqkv + blockIdx.x * 6144) : "memory");
    asm volatile("cp.async.bulk.prefetch.L2.global [%0], 16384;" ::"l"(x + blockIdx.x * 8192) : "memory");
  }
  __shared__ float red[8][16];
  const int b = blockIdx.x, tid = threadIdx.x, lane = tid & 31, warp = tid >> 5;
  {
    const __nv_bfloat16* w; int ld, out;
    if (b < 96) { w = wqkv + b * 16; ld = 1536; out = b * 16; }
    else if (b < 128) { w = wq + (b - 96) * 16; ld = 512; out = 1536 + (b - 96) * 16; }
    else { w = (b == 128) ? wk : wv; ld = 16; out = 2048 + (b - 128) * 16; }
    const int half = tid & 1, r0 = tid >> 1;
    float acc[8];
#pragma unroll
    for (int i = 0; i < 8; i++) acc[i] = 0.f;
#pragma unroll
    for (int j = 0; j < 4; j++) {
      uint4 v = __ldg(reinterpret_cast<const uint4*>(w + (size_t)(r0 + 128 * j) * ld + half * 8));
      if (b >= 128) *reinterpret_cast<uint4*>(g_wkv + (r0 + 128 * j) * 32 + (b - 128) * 16 + half * 8) = v;
      acc[0] += bf_lo(v.x); acc[1] += bf_hi(v.x); acc[2] += bf_lo(v.y); acc[3] += bf_hi(v.y);
      acc[4] += bf_lo(v.z); acc[5] += bf_hi(v.z); acc[6] += bf_lo(v.w); acc[7] += bf_hi(v.w);
    }
#pragma unroll
    for (int i = 0; i < 8; i++) {
#pragma unroll
      for (int o = 2; o < 32; o <<= 1) acc[i] += __shfl_xor_sync(0xffffffffu, acc[i], o);
    }
    if (lane < 2) {
#pragma unroll
      for (int i = 0; i < 8; i++) red[warp][lane * 8 + i] = acc[i];
    }
    __syncthreads();
    if (tid < 16) {
      float s = 0.f;
#pragma unroll
      for (int w8 = 0; w8 < 8; w8++) s += red[w8][tid];
      g_colsum[out + tid] = s;
    }
  }
  if (b < 128) {
#pragma unroll
    for (int j = 0; j < 2; j++) {
      const int row = b * 16 + warp * 2 + j;
      const uint4* p = reinterpret_cast<const uint4*>(x + (size_t)row * D_ + lane * 16);
      uint4 v0 = __ldg(p), v1 = __ldg(p + 1);
      uint32_t u[8] = {v0.x, v0.y, v0.z, v0.w, v1.x, v1.y, v1.z, v1.w};
      float s = 0.f, q = 0.f;
#pragma unroll
      for (int i = 0; i < 8; i++) {
        float a = bf_lo(u[i]), c = bf_hi(u[i]);
        s += a + c; q = fmaf(a, a, fmaf(c, c, q));
      }
      s += __shfl_xor_sync(0xffffffffu, s, 1); q += __shfl_xor_sync(0xffffffffu, q, 1);
      s += __shfl_xor_sync(0xffffffffu, s, 2); q += __shfl_xor_sync(0xffffffffu, q, 2);
      if ((lane & 3) == 0) g_stats[row * 8 + (lane >> 2)] = make_float2(s, q);
    }
  }
  if (b < 128 && tid < 64) asm volatile("prefetch.global.L2 [%0];" ::"l"((tid < 32 ? woa : wob) + (b * 32 + lane) * 64));
  TM(0, 4);
}

__device__ __forceinline__ int tok0(int r, int rb) { return (rb >> 2) * 512 + r * 256 + (rb & 3) * 64; }
__device__ __forceinline__ int key_pos(int token) {
  const int r = (token >> 8) & 1, rb = ((token >> 9) << 2) | ((token >> 6) & 3), row = token & 63;
  return (16 * r + (row >> 2)) * 64 + rb * 4 + (row & 3);
}
__device__ __forceinline__ float sq_norm16(const uint4& a, const uint4& b) {
  const uint32_t u[8] = {a.x, a.y, a.z, a.w, b.x, b.y, b.z, b.w};
  __half2 n = __hmul2(*reinterpret_cast<const __half2*>(&u[0]), *reinterpret_cast<const __half2*>(&u[0]));
#pragma unroll
  for (int i = 1; i < 8; i++) n = __hfma2(*reinterpret_cast<const __half2*>(&u[i]), *reinterpret_cast<const __half2*>(&u[i]), n);
  return __low2float(n) + __high2float(n);
}
__device__ __forceinline__ uint32_t hsub2(uint32_t a, uint32_t b) {
  uint32_t d; asm("sub.rn.f16x2 %0, %1, %2;" : "=r"(d) : "r"(a), "r"(b)); return d;
}
__device__ __forceinline__ uint32_t hfma2(uint32_t a, uint32_t b, uint32_t c) {
  uint32_t d; asm("fma.rn.f16x2 %0, %1, %2, %3;" : "=r"(d) : "r"(a), "r"(b), "r"(c)); return d;
}
__device__ __forceinline__ uint32_t hadd2(uint32_t a, uint32_t b) {
  uint32_t d; asm("add.rn.f16x2 %0, %1, %2;" : "=r"(d) : "r"(a), "r"(b)); return d;
}
__device__ __forceinline__ __half2 q_norms(const uint32_t (&v)[4]) {
  const uint32_t n0 = hfma2(v[0], v[0], hfma2(v[2], v[2], 0u)), n1 = hfma2(v[1], v[1], hfma2(v[3], v[3], 0u));
  uint32_t n = hadd2(__byte_perm(n0, n1, 0x5410), __byte_perm(n0, n1, 0x7632));
  n = hadd2(n, __shfl_xor_sync(0xffffffffu, n, 1));
  n = hadd2(n, __shfl_xor_sync(0xffffffffu, n, 2));
  return *reinterpret_cast<__half2*>(&n);
}
__device__ __forceinline__ void store_k(uint4* dst, const uint4& a, const uint4& b) {
  dst[0] = make_uint4(a.x, b.x, a.y, b.y); dst[8] = make_uint4(a.z, b.z, a.w, b.w);
}
template <bool F16, int N>
__device__ __forceinline__ void proj_cvt(uint32_t (&r)[4], const float (&acc)[N], int j  , const float* cs,
                                         float mu0, float f0, float mu1, float f1) {
#pragma unroll
  for (int e = 0; e < 2; e++) {
    const float2 c = *reinterpret_cast<const float2*>(cs + (j + e) * 8);
    const float a0 = fmaf(-mu0, c.x, acc[(j + e) * 4 + 0]) * f0, a1 = fmaf(-mu0, c.y, acc[(j + e) * 4 + 1]) * f0;
    const float a2 = fmaf(-mu1, c.x, acc[(j + e) * 4 + 2]) * f1, a3 = fmaf(-mu1, c.y, acc[(j + e) * 4 + 3]) * f1;
    r[e * 2] = F16 ? pack_f16(a0, a1) : pack_bf16(a0, a1);
    r[e * 2 + 1] = F16 ? pack_f16(a2, a3) : pack_bf16(a2, a3);
  }
}
template <int N>
__device__ __forceinline__ void stage_k(const float (&acc)[N], int j, uint32_t addr, const float* cs, float mu0, float f0, float mu1, float f1) {
  uint32_t r[4];
  proj_cvt<true>(r, acc, j, cs, mu0, f0, mu1, f1);
  stsm4(addr + j * 16, r[0], r[1], r[2], r[3]);
}
template <int NH, int N>
__device__ __forceinline__ void emit_v(const float (&acc)[N], int j0, int hb, int r, int rb, int row, int c, const float* cs, float mu0,
                                       float f0, float mu1, float f1) {
  uint2* dst = reinterpret_cast<uint2*>(g_v) + (hb * (S_ * 2) + (c & 1) * S_ + (16 * r + (row >> 2)) * 64 + rb * 4 + (row & 3)) * 2 + (c >> 1);
#pragma unroll
  for (int h = 0; h < NH; h++) {
    uint32_t v[4];
    proj_cvt<false>(v, acc, j0 + 2 * h, cs, mu0, f0, mu1, f1);
    dst[h * (S_ * 4)] = make_uint2(v[0], v[2]); dst[h * (S_ * 4) + 256] = make_uint2(v[1], v[3]);
  }
}
__device__ __forceinline__ void emit_q(const float (&acc)[32], int layer, int hg, int token, int c, const float* cs, float mu0, float rs0,
                                       float mu1, float rs1) {
  uint2* dst = reinterpret_cast<uint2*>(g_q) + (((layer & 1) * H_ + hg * 4) * (S_ * 2) + (token >> 3) * 16 + (c >> 1) * 8 + (token & 7)) * 2 + (c & 1);
  __half2 mx = __float2half2_rn(0.f);
#pragma unroll
  for (int h = 0; h < 4; h++) {
    uint32_t v[4];
    proj_cvt<true>(v, acc, 2 * h, cs, mu0, rs0 * QSCALE, mu1, rs1 * QSCALE);
    dst[h * (S_ * 4)] = make_uint2(v[0], v[2]); dst[h * (S_ * 4) + 32] = make_uint2(v[1], v[3]);
    mx = __hmax2_nan(mx, q_norms(v));
  }
  const unsigned m = __reduce_max_sync(0xffffffffu, __float_as_uint(__half2float(__hmax_nan(__low2half(mx), __high2half(mx)))) & 0x7fffffffu);
  if ((threadIdx.x & 31) == 0) g_nq[(layer * 8 + hg) * 128 + (token >> 4)] = __uint_as_float(m);
}
template <int NI>
__device__ __forceinline__ void emit_k(uint32_t a, uint32_t ap, int layer, int head, int token, int pos) {
  uint4* dst = g_k + ((layer & 1) * H_ + head) * (S_ * 2) + (pos >> 3) * 16 + (pos & 7);
  uint4 v[2 * NI];
  unsigned m[NI];
#pragma unroll
  for (int i = 0; i < 2 * NI; i++) v[i] = lds128(a + (i >> 1) * 64 + (i & 1) * 16);
#pragma unroll
  for (int i = 0; i < NI; i++) m[i] = __reduce_max_sync(0xffffffffu, __float_as_uint(sq_norm16(v[2 * i], v[2 * i + 1])) & 0x7fffffffu);
  if (ap) {
#pragma unroll
    for (int i = 0; i < 2 * NI; i++) {
      const uint4 p = lds128(ap + (i >> 1) * 64 + (i & 1) * 16);
      v[i] = make_uint4(hsub2(v[i].x, p.x), hsub2(v[i].y, p.y), hsub2(v[i].z, p.z), hsub2(v[i].w, p.w));
    }
  }
#pragma unroll
  for (int i = 0; i < NI; i++) {
    store_k(dst + i * 4 * S_, v[2 * i], v[2 * i + 1]);
    if ((threadIdx.x & 31) == 0) g_nk[(layer * H_ + head + 2 * i) * 64 + (token >> 5)] = __uint_as_float(m[i]);
  }
}

#define QC 3
constexpr int G1_NB = 8, G1_B = 131072, G1_STG = G1_B + G1_NB * 8192, G1_P = 144, G1_CS = G1_STG + 128 * G1_P, G1_BAR = G1_CS + 768;
constexpr int G1A_SMEM = G1_BAR + 256 + 1024;
__global__ void __maxnreg__(144) g1a_kernel(const __grid_constant__ CUtensorMap mx, const __grid_constant__ CUtensorMap mw) {
  extern __shared__ uint8_t smem_raw[];
  const uint32_t sbase = (s2u(smem_raw) + 1023) & ~1023u;
  const uint32_t bar_a = sbase + G1_BAR, bar_b = bar_a + 64, bar_e = bar_b + 32;
  float* cs = reinterpret_cast<float*>(smem_raw + (sbase + G1_CS - s2u(smem_raw)));
  const int tid = threadIdx.x, lane = tid & 31;
  const int warp = __shfl_sync(0xffffffffu, tid >> 5, 0);
  const int nb = blockIdx.x & 7, rb = blockIdx.x >> 3;
  TM(1, 0);
  if (tid == 0) {
    for (int i = 0; i < 8; i++) mbar_init(bar_a + i * 8, 1);
    for (int i = 0; i < 4; i++) { mbar_init(bar_b + i * 8, 1); mbar_init(bar_e + i * 8, 8); }
    fence_bar_init();
  }
  __syncthreads();
  if (warp == 8) {
#pragma unroll
    for (int n = 0; n < 12; n++) {
      const int s = n & 3;
      const uint32_t st = sbase + G1_B + s * 16384;
      if (n >= 4) mbar_wait(bar_e + s * 8, (n / 4 - 1) & 1);
      if (elect_one()) {
        mbar_expect(bar_b + s * 8, 16384);
        tma_load(st, &mw, (n < 8 ? 512 : 0) + nb * 64, n < 8 ? n * 64 : s * 128, bar_b + s * 8);
        tma_load(st + 8192, &mw, (n < 8 ? 1024 : 0) + nb * 64, n < 8 ? n * 64 : s * 128 + 64, bar_b + s * 8);
        if (n < 4) {
#pragma unroll
          for (int c = n; c < 8; c += (n == 3 ? 1 : 8)) {
            mbar_expect(bar_a + c * 8, 16384);
            tma_load(sbase + c * 16384, &mx, c * 64, tok0(0, rb), bar_a + c * 8);
            tma_load(sbase + c * 16384 + 8192, &mx, c * 64, tok0(1, rb), bar_a + c * 8);
          }
        }
      }
    }
    return;
  }
  const int wg = warp >> 2;
  float acc0[32], acc1[32], acc2[32];
  float mu0 = 0.f, rs0 = 0.f, mu1 = 0.f, rs1 = 0.f;
  auto prep_results = [&]() {
      pdl_wait();
      pdl_launch();
      if (tid < 192) cs[tid] = __ldcg(g_colsum + (tid < 128 ? 512 + (tid >> 6) * 512 : 0) + nb * 64 + (tid & 63));
      const int row0 = tok0(wg, rb) + (warp & 3) * 16 + (lane >> 2);
      row_stats(0, row0, mu0, rs0); row_stats(0, row0 + 8, mu1, rs1);
  };
#pragma unroll
  for (int c = 0; c < 8; c++) {
    mbar_wait(bar_a + c * 8, 0);
    mbar_wait(bar_b + (c & 3) * 8, c >> 2);
    if (c == 0) TM(1, 2);
    const uint64_t da = mkdesc(sbase + c * 16384 + wg * 8192, 16, 1024, 1), db = mkdesc(sbase + G1_B + (c & 3) * 16384, 8192, 1024, 1);
    wg_fence();
#pragma unroll
    for (int k = 0; k < 4; k++) {
      if (c + k == 0) wgmma_gemm_n128_first(acc0, acc1, da, db);
      else wgmma_gemm_n128(acc0, acc1, da + k * 2, db + k * 128);
    }
    wg_commit();
    if (c > 0) {
      wg_wait<1>();
      if (elect_one()) mbar_arrive(bar_e + ((c - 1) & 3) * 8);
    }
  }
  wg_wait<0>();
  if (elect_one()) mbar_arrive(bar_e + 24);
  pin(acc0); pin(acc1);
  TM(1, 1);
#pragma unroll
  for (int c = 0; c < 8; c++) {
    if (!(c & 1)) mbar_wait(bar_b + (c >> 1) * 8, 0);
    const uint64_t da = mkdesc(sbase + c * 16384 + wg * 8192, 16, 1024, 1), db = mkdesc(sbase + G1_B + c * 8192, 8192, 1024, 1);
    if (!(c & 1)) wg_fence();
#pragma unroll
    for (int k = 0; k < 4; k++) {
      if (c + k == 0) wgmma_gemm_n64_first(acc2, da, db);
      else wgmma_gemm_n64(acc2, da + k * 2, db + k * 128);
    }
    if (c == QC) {
      wg_commit();
      prep_results();
      named_sync(1, 256);
      const uint32_t addr = sbase + G1_STG + (warp * 16 + (lane & 15)) * G1_P + (lane >> 4) * 16;
#pragma unroll
      for (int j = 0; j < 8; j += 2) stage_k(acc0, j, addr, cs + (lane & 3) * 2, mu0, rs0, mu1, rs1);
    }
  }
  wg_commit();
  emit_v<4>(acc1, 0, nb * 4, wg, rb, (warp & 3) * 16 + (lane >> 2), lane & 3, cs + 64 + (lane & 3) * 2, mu0, rs0, mu1, rs1);
  named_sync(1, 256);
  {
    const int trow = (warp & 3) * 32 + lane, token = tok0(trow >> 6, rb) + (trow & 63);
    const uint32_t a = sbase + G1_STG + trow * G1_P + wg * 32;
    emit_k<2>(a, trow >= 4 ? a - 4 * G1_P : 0u, 0, nb * 4 + wg, token, key_pos(token));
  }
  wg_wait<0>();
  pin(acc2);
  TM(1, 3);
  emit_q(acc2, 0, nb, tok0(wg, rb) + (warp & 3) * 16 + (lane >> 2), lane & 3, cs + 128 + (lane & 3) * 2, mu0, rs0, mu1, rs1);
  TM(1, 4);
}

#define MMASK 0x0F80u
constexpr uint32_t MUFU_MASK = MMASK;
constexpr float TINY = 1.17549435e-38f;
constexpr float EXP_MAGIC = 383.0f + 0.65f / 128.0f;
constexpr uint32_t POLY_A = 0x5a835a83u, POLY_B = 0x92a192a1u, POLY_C = 0x800b800bu;
#define ODIRECT 1
#define XDIRECT 1
#define VV 18
#define L6 1
#define PBO 1
#define WB 3
#define FP 1
#define MX 1
#define FL 0
#define SCHED 0x211033203001ull
constexpr float SCORE_LIMIT = 116.f;

__device__ __forceinline__ void exp_step(const float (&s)[32], uint32_t (&p)[16], uint32_t pb) {
#pragma unroll
  for (int i = 0; i < 16; i++) {
    if ((MUFU_MASK >> i) & 1) {
      float a, b;
      asm("ex2.approx.ftz.f32 %0, %1;" : "=f"(a) : "f"(s[2 * i]));
      asm("ex2.approx.ftz.f32 %0, %1;" : "=f"(b) : "f"(s[2 * i + 1]));
      p[i] = pack_bf16(a, b);
    } else {
      uint32_t z, u, h;
      asm("prmt.b32 %0, %1, %2, 0x6521;" : "=r"(z) : "r"(__float_as_uint(s[2 * i])), "r"(__float_as_uint(s[2 * i + 1])));
      asm("fma.rn.f16x2 %0, %1, %2, %3;" : "=r"(u) : "r"(z & 0x007f007fu), "r"(POLY_A), "r"(pb));
      asm("fma.rn.f16x2 %0, %1, %1, %2;" : "=r"(h) : "r"(u), "r"(POLY_C));
      p[i] = z - h;
    }
  }
}

__device__ __forceinline__ void pv4(float (&o)[12], const uint32_t (&p)[16], uint64_t dv) {
#pragma unroll
  for (int j = 0; j < 4; j++) wgmma_pv_n24(o, p[4 * j], p[4 * j + 1], p[4 * j + 2], p[4 * j + 3], dv + j * 16);
}
template <bool PV>
__device__ __forceinline__ void att_step(float (&s)[32], float (&o)[12], uint32_t (&pin_)[16], uint32_t (&pout)[16], uint64_t dq,
                                         uint64_t dk, uint64_t dv, uint32_t pb) {
  pin(s);
  if (PV) pin(pin_);
  wg_fence();
  wgmma_qk_n64(s, dq, dk);
  wg_commit();
  if (PV) {
#pragma unroll
    for (int j = 0; j < 4; j++) wgmma_pv_n24(o, pin_[4 * j], pin_[4 * j + 1], pin_[4 * j + 2], pin_[4 * j + 3], dv + j * 16);
    wg_commit();
    wg_wait<1>();
  } else {
    wg_wait<0>();
  }
  pin(s);
  exp_step(s, pout, pb);
  pin(pout);
}

constexpr int M_STAGE = 0;
constexpr int M_STG = 65536, STG_PITCH = 144;
constexpr int M_KV = 74752;
constexpr int M_Q = M_KV + 17 * 8192;
constexpr int M_CS = M_Q + 16384, M_KTAIL = M_CS + 768, M_ROW = M_KTAIL + 512, M_BAR = M_ROW + 512;
constexpr int MEGA_SMEM = M_BAR + 256;
__device__ __forceinline__ int k_unit(int b, int j) { return j == 0 ? 4 + 4 * b : 9 + 2 * b; }
__device__ __forceinline__ int v_unit(int b, int j) { return (j + 1) * (1 + 2 * b); }
constexpr int B_FULL = 0, B_EMPTY = 32, B_Q = 64, B_CHK = 80, B_FREE0 = 88, B_ODONE = 96, B_RES = 112, B_PRE = 120,
              B_TURN = 128, B_EPI = 160, B_FULLR = 192, B_KV = 224;
constexpr int M_CHK = M_KV - 16;

struct MegaParams {
  CUtensorMap m[8];
  uint32_t poly_b, pad;
  const __nv_bfloat16* x0;
  const __nv_bfloat16* wqkv; const __nv_bfloat16* wq; const __nv_bfloat16* wk;
  __nv_bfloat16* out;
};

__device__ __forceinline__ void cnt_signal(int idx, unsigned n = 1) {
  if (elect_one()) asm volatile("red.release.gpu.global.add.u32 [%0], %1;" ::"l"(g_cnt + idx * CNT_STRIDE), "r"(n) : "memory");
}
#define POLL_NS 0
__device__ __forceinline__ void cnt_wait(int idx, unsigned target) {
  unsigned v;
  const uint32_t t0 = clock32();
  while (true) {
    asm volatile("ld.acquire.gpu.global.u32 %0, [%1];" : "=r"(v) : "l"(g_cnt + idx * CNT_STRIDE) : "memory");
    if (v >= target) break;
    if (clock32() - t0 > WAIT_LIMIT) GIVE_UP(0x10000000 + idx * 256 + v);
    if (POLL_NS) __nanosleep(POLL_NS);
  }
  asm volatile("fence.proxy.async.global;" ::: "memory");
}

__device__ __forceinline__ void cnt_done() {
  unsigned old = 0;
  if ((threadIdx.x & 31) == 0)
    asm volatile("atom.acq_rel.gpu.global.add.u32 %0, [%1], 1;" : "=r"(old) : "l"(g_cnt + CNT_DONE * CNT_STRIDE) : "memory");
  if (__shfl_sync(0xffffffffu, old, 0) == gridDim.x - 1)
    for (int i = threadIdx.x & 31; i < CNT_N; i += 32) g_cnt[i * CNT_STRIDE] = 0u;
}

__device__ __forceinline__ void att_fallback(const MegaParams& P, int layer, int head, int row0, __nv_bfloat16* sk, int bar_id) {
  int t;
  asm volatile("mov.u32 %0, %%tid.x;" : "=r"(t));
  t &= 127;
  const int hf = t & 1;
  asm volatile("" : "+r"(layer), "+r"(head), "+r"(row0));
  const __nv_bfloat16* x = layer == 0 ? P.x0 : g_x + (size_t)(layer - 1) * S_ * D_;
  const bool mqa = layer & 1;
  const __nv_bfloat16* vimg = reinterpret_cast<const __nv_bfloat16*>(g_v + (size_t)((layer & 1) * H_ + (mqa ? 0 : head)) * (S_ * 2));
  float q[16], o[16], acc[16];
  float m = -INFINITY, l = 0.f;
#pragma unroll
  for (int d = 0; d < 16; d++) { o[d] = 0.f; q[d] = 0.f; }
#pragma unroll 1
  for (int ch = -1; ch < 32; ch++) {
    const int token = ch < 0 ? row0 + (t >> 1) : ch * 64 + (t >> 1);
    const __nv_bfloat16* w = ch < 0 ? (mqa ? P.wq : P.wqkv) + head * 16 : (mqa ? P.wk : P.wqkv + 512 + head * 16);
    const int ld = mqa ? (ch < 0 ? 512 : 16) : 1536;
    float mu, rs;
    row_stats(layer, token, mu, rs);
#pragma unroll
    for (int d = 0; d < 16; d++) acc[d] = 0.f;
#pragma unroll 1
    for (int k = hf * 256; k < hf * 256 + 256; k++) {
      const unsigned short xr = __ldcg(reinterpret_cast<const unsigned short*>(x) + (size_t)token * D_ + k);
      const float xn = __bfloat162float(__float2bfloat16((__uint_as_float((uint32_t)xr << 16) - mu) * rs));
#pragma unroll
      for (int d = 0; d < 16; d++) acc[d] = fmaf(xn, __bfloat162float(w[(size_t)k * ld + d]), acc[d]);
    }
#pragma unroll
    for (int d = 0; d < 16; d++) acc[d] = __bfloat162float(__float2bfloat16(acc[d] + __shfl_xor_sync(0xffffffffu, acc[d], 1)));
    if (ch < 0) {
#pragma unroll
      for (int d = 0; d < 16; d++) q[d] = acc[d];
      continue;
    }
    named_sync(bar_id, 128);
    if (hf == 0) {
#pragma unroll
      for (int d = 0; d < 16; d++) sk[(t >> 1) * 16 + d] = __float2bfloat16(acc[d]);
    }
    named_sync(bar_id, 128);
#pragma unroll 1
    for (int j = hf * 32; j < hf * 32 + 32; j++) {
      float sc = 0.f;
#pragma unroll
      for (int d = 0; d < 16; d++) sc = fmaf(q[d], __bfloat162float(sk[j * 16 + d]), sc);
      sc *= 0.25f;
      if (sc > m || sc != sc) {
        const float a = __expf(m - sc);
        l *= a;
#pragma unroll
        for (int d = 0; d < 16; d++) o[d] *= a;
        m = sc;
      }
      const float p = __expf(sc - m);
      l += p;
      const int pos = key_pos(ch * 64 + j);
#pragma unroll
      for (int d = 0; d < 16; d++) {
        const unsigned short vr = __ldcg(reinterpret_cast<const unsigned short*>(vimg) + ((d >> 1) & 1) * (S_ * 8) + pos * 8 + ((d >> 2) & 1) * 4 + (d >> 3) * 2 + (d & 1));
        o[d] = fmaf(p, __uint_as_float((uint32_t)vr << 16), o[d]);
      }
    }
  }
  const float m2 = __shfl_xor_sync(0xffffffffu, m, 1), mm = fmaxf(m, m2), a = __expf(m - mm);
  l *= a; l += __shfl_xor_sync(0xffffffffu, l, 1);
  const float inv = 1.f / l;
  __nv_bfloat16* dst = g_o + (size_t)(row0 + (t >> 1)) * D_ + head * 16;
#pragma unroll
  for (int d = 0; d < 16; d++) {
    float v = o[d] * a; v += __shfl_xor_sync(0xffffffffu, v, 1);
    if ((d >> 3) == hf) dst[d] = __float2bfloat16(v * inv);
  }
}

__device__ __forceinline__ const CUtensorMap* b_map(const MegaParams& P, int code) {
  const int l = code >> 3, p = code & 3;
  return &P.m[p == 0 ? 5 + (l & 1) : 3 - (l & 1)];
}
__device__ __forceinline__ int b_col(int code) {
  const int p = code & 3, ct = blockIdx.x & 7;
  return (p == 3 ? 0 : p * 512) + ct * 64;
}
__device__ __forceinline__ void issue_b(uint32_t sbase, const CUtensorMap* m, int col, int st, int c) {
  mbar_expect(sbase + M_BAR + B_FULL + st * 8, 16384);
  tma_load(sbase + M_STAGE + st * 16384 + 8192, m, col, c * 64, sbase + M_BAR + B_FULL + st * 8);
}
__device__ __forceinline__ void issue_a(uint32_t sbase, const CUtensorMap* m, int row, int st, int c) {
  tma_load(sbase + M_STAGE + st * 16384, m, c * 64, row, sbase + M_BAR + B_FULL + st * 8);
}
__device__ __forceinline__ void load_kv(uint32_t sbase, int l, int r) {
  const size_t hb = (size_t)((l & 1) * H_ + ((l & 1) ? 0 : blockIdx.x >> 2)) * 65536;
  const uint8_t* gk = reinterpret_cast<const uint8_t*>(g_k) + hb;
  const uint8_t* gv = reinterpret_cast<const uint8_t*>(g_v) + hb;
  if (elect_one()) {
#pragma unroll
    for (int j = 0; j < 2; j++) {
      const int b = r * 2 + j;
      const uint32_t bar = sbase + M_BAR + B_KV + b * 8;
      mbar_expect(bar, 32768);
      bulk_load(sbase + M_KV + k_unit(b, 0) * 8192, gk + b * 16384, 8192, bar);
      bulk_load(sbase + M_KV + v_unit(b, 0) * 8192, gv + b * 8192, 8192, bar);
      bulk_load(sbase + M_KV + v_unit(b, 1) * 8192, gv + 32768 + b * 8192, 8192, bar);
      bulk_load(sbase + M_KV + k_unit(b, 1) * 8192, gk + b * 16384 + 8192, 8192, bar);
    }
  }
}
__device__ __forceinline__ void load_q(uint32_t sbase, int l, int r) {
  const uint32_t bar = sbase + M_BAR + B_Q + r * 8;
  if (elect_one()) {
    mbar_expect(bar, 8192);
    bulk_load(sbase + M_Q + r * 8192,
              reinterpret_cast<const uint8_t*>(g_q) + (size_t)((l & 1) * H_ + (blockIdx.x >> 2)) * 65536 + (blockIdx.x & 3) * 16384 + r * 8192,
              8192, bar);
  }
}

__device__ __forceinline__ bool pass_exists(int job, int p) { return p == 0 || (job < 6 && (p == 3 || (job & 2))); }
__device__ __forceinline__ int next_pass(int code) {
  const int job = code >> 2, p = code & 3;
  if (p == 0 && pass_exists(job, 1)) return code + 1;
  if (p == 1 && pass_exists(job, 2)) return code + 1;
  if (p < 3 && pass_exists(job, 3)) return job * 4 + 3;
  return job * 4 + 4;
}
__device__ __forceinline__ int prev_pass(int code) {
  const int job = code >> 2, p = code & 3;
  if (p == 0) return job > 6 ? (job - 1) * 4 : (job - 1) * 4 + 3;
  if (p == 3 && pass_exists(job, 2)) return code - 1;
  if (p >= 2 && pass_exists(job, 1)) return job * 4 + 1;
  return job * 4;
}

__device__ __forceinline__ int res_unit(int c) { return ((0xFEDCB964u >> (4 * c)) & 15) + 1; }
__device__ __forceinline__ uint32_t res_parity(int code) {
  return (code & 8) ? code & 1 : (code >> 1) & 1;
}
__device__ __forceinline__ void proj_pass(const MegaParams& P, uint8_t* sm, uint32_t sbase, int code, int wg) {
  const uint32_t s_bar = sbase + M_BAR;
  const bool first_proj = (code & 3) == ((code & 8) ? 1 : 3);
  const int prev = (code & 3) == 0 ? (code < 28 ? code - 1 : code - 4) : (first_proj ? code & ~3 : code - 1);
  const int wu = __shfl_sync(0xffffffffu, (threadIdx.x >> 5) & 3, 0);
  const CUtensorMap* mb = b_map(P, code);
  const CUtensorMap* ma = &P.m[(code & 3) == 0 ? 1 : 0];
  const int colb = b_col(code), rowa = tok0((code >> 2) & 1, blockIdx.x >> 3) + ((code & 3) == 0 ? 0 : (code >> 3) * S_);
  if (code > 0) mbar_wait_long(s_bar + B_TURN + (prev & 3) * 8, (prev >> 2) & 1);
  float acc[32];
  const bool res = code & 4;
  const uint32_t rpar = res_parity(code);
  float4 sv0 = make_float4(0.f, 0.f, 0.f, 0.f), sv1 = sv0;
  auto stats_load = [&]() {
    const float4* sp = reinterpret_cast<const float4*>(g_stats + (S_ + rowa) * 8) + (threadIdx.x & 127) * 2;
    sv0 = __ldcg(sp); sv1 = __ldcg(sp + 1);
  };
  if (res) {
#pragma unroll
    for (int c = 0; c < 8; c++) {
      if (!(c & 1)) mbar_wait(s_bar + B_FULLR + (c >> 1) * 8, rpar);
      const uint64_t da = mkdesc(sbase + M_KV + res_unit(c) * 8192, 16, 1024, 1), db = mkdesc(sbase + M_STAGE + c * 8192, 8192, 1024, 1);
      if (!(c & 1)) wg_fence();
#pragma unroll
      for (int k = 0; k < 4; k++) {
        if (c + k == 0) wgmma_gemm_n64_first(acc, da, db);
        else wgmma_gemm_n64(acc, da + k * 2, db + k * 128);
      }
      if (c & 1) wg_commit();
      if (c == 1 && first_proj) stats_load();
      if (c >= 3 && (c & 1)) {
        wg_wait<1>();
        if (elect_one()) mbar_arrive(s_bar + B_EMPTY + (c / 2 - 1) * 8);
      }
    }
    wg_wait<0>();
  } else {
#pragma unroll
    for (int c = 0; c < 8; c++) {
      const uint32_t st = sbase + M_STAGE + (c & 3) * 16384;
      mbar_wait(s_bar + B_FULL + (c & 3) * 8, c >> 2);
      const uint64_t da = mkdesc(st, 16, 1024, 1), db = mkdesc(st + 8192, 8192, 1024, 1);
      wg_fence();
#pragma unroll
      for (int k = 0; k < 4; k++) {
        if (c + k == 0) wgmma_gemm_n64_first(acc, da, db);
        else wgmma_gemm_n64(acc, da + k * 2, db + k * 128);
      }
      wg_commit();
      if (c >= 1 && c <= 3) {
        wg_wait<1>();
        named_sync(wg + 1, 128);
        if (wu == c - 1 && elect_one()) { issue_b(sbase, mb, colb, c - 1, c + 3); issue_a(sbase, ma, rowa, c - 1, c + 3); }
      }
      if (c == 3) {
        wg_wait<0>();
        named_sync(wg + 1, 128);
        if (wu == 3 && elect_one()) { issue_b(sbase, mb, colb, 3, 7); issue_a(sbase, ma, rowa, 3, 7); }
        if (first_proj) stats_load();
      }
      if (c >= 5) {
        wg_wait<1>();
        if (elect_one()) mbar_arrive(s_bar + B_EMPTY + (c - 5) * 8);
      }
    }
    wg_wait<0>();
  }
  pin(acc);
  if (first_proj) {
    float su = (sv0.x + sv0.z) + (sv1.x + sv1.z), sq = (sv0.y + sv0.w) + (sv1.y + sv1.w);
    su += __shfl_xor_sync(0xffffffffu, su, 1); sq += __shfl_xor_sync(0xffffffffu, sq, 1);
    const float mu = su * (1.f / D_);
    reinterpret_cast<float2*>(sm + M_ROW)[(threadIdx.x & 127) >> 1] = make_float2(mu, rsqrtf(fmaxf(sq * (1.f / D_) - mu * mu, 0.f) + LN_EPS));
    __syncwarp();
  }
  if (elect_one()) { mbar_arrive(s_bar + B_EMPTY + 24); mbar_arrive(s_bar + B_TURN + (code & 3) * 8); }
  int t;
  asm volatile("mov.u32 %0, %%tid.x;" : "=r"(t));
  t &= 127;
  const int lane = t & 31, w4 = t >> 5;
  const int l = code >> 3, r = (code >> 2) & 1, p = code & 3;
  const int rb = blockIdx.x >> 3, ct = blockIdx.x & 7, row0 = tok0(r, rb);
  const uint32_t stg = sbase + M_STG;
  if (p == 0) {
    mbar_wait(s_bar + B_RES, r);
    const uint32_t ra = stg + (w4 * 16 + (lane & 15)) * 128;
    float s0 = 0.f, q0 = 0.f, s1 = 0.f, q1 = 0.f;
#pragma unroll
    for (int j = 0; j < 8; j += 2) {
      const uint32_t a = ra + (((j + (lane >> 4)) ^ (lane & 7)) << 4);
      uint32_t y[4];
      ldsm4(a, y[0], y[1], y[2], y[3]);
#pragma unroll
      for (int e = 0; e < 4; e++) {
        y[e] = hadd2_bf16(y[e], pack_bf16(acc[4 * j + 2 * e], acc[4 * j + 2 * e + 1]));
        const float lo = bf_lo(y[e]), hi = bf_hi(y[e]);
        if (e & 1) { s1 += lo + hi; q1 = fmaf(lo, lo, fmaf(hi, hi, q1)); }
        else { s0 += lo + hi; q0 = fmaf(lo, lo, fmaf(hi, hi, q0)); }
      }
      stsm4(a, y[0], y[1], y[2], y[3]);
    }
    __syncwarp();
    __nv_bfloat16* xout = (l == 3 ? P.out : g_x + (size_t)l * S_ * D_) + (size_t)(row0 + w4 * 16 + (lane >> 3)) * D_ + ct * 64 + (lane & 7) * 8;
#pragma unroll
    for (int i = 0; i < 4; i++) {
      const int rr = i * 4 + (lane >> 3);
      *reinterpret_cast<uint4*>(xout + (size_t)i * 4 * D_) = lds128(stg + (w4 * 16 + rr) * 128 + (((lane & 7) ^ (rr & 7)) << 4));
    }
    if (l < 3) {
      const bool lower = lane & 2;
      float su = (lower ? s1 : s0) + __shfl_xor_sync(0xffffffffu, lower ? s0 : s1, 2);
      float sq = (lower ? q1 : q0) + __shfl_xor_sync(0xffffffffu, lower ? q0 : q1, 2);
      su += __shfl_xor_sync(0xffffffffu, su, 1); sq += __shfl_xor_sync(0xffffffffu, sq, 1);
      if (!(lane & 1)) g_stats[((l + 1) * S_ + row0 + w4 * 16 + (lane >> 2) + (lane & 2) * 4) * 8 + ct] = make_float2(su, sq);
      if (XDIRECT && (r || XDIRECT == 2)) {
        named_sync(wg + 1, 128);
        if (wu == 0) cnt_signal(CNT_X + (code >> 2) * 16 + rb, 4);
      }
    }
  } else {
    mbar_wait(s_bar + B_PRE, r);
    const float2 st0 = reinterpret_cast<const float2*>(sm + M_ROW)[w4 * 16 + (lane >> 2)];
    const float2 st1 = reinterpret_cast<const float2*>(sm + M_ROW)[w4 * 16 + (lane >> 2) + 8];
    const float* cs = reinterpret_cast<const float*>(sm + M_CS) + (p - 1) * 64 + (lane & 3) * 2;
    if (p == 3) {
      emit_q(acc, l + 1, ct, row0 + w4 * 16 + (lane >> 2), lane & 3, cs, st0.x, st0.y, st1.x, st1.y);
    } else if (p == 2) {
      emit_v<4>(acc, 0, ((l + 1) & 1) * H_ + ct * 4, r, rb, w4 * 16 + (lane >> 2), lane & 3, cs, st0.x, st0.y, st1.x, st1.y);
    } else {
      mbar_wait(s_bar + B_EPI, r);
      const uint32_t saddr = stg + (w4 * 16 + (lane & 15)) * STG_PITCH + (lane >> 4) * 16;
#pragma unroll
      for (int j = 0; j < 8; j += 2) stage_k(acc, j, saddr, cs, st0.x, st0.y, st1.x, st1.y);
      named_sync(wg + 1, 128);
      const int row = t & 63, hh = t >> 6;
      const uint32_t a = stg + row * STG_PITCH + hh * 32;
      emit_k<2>(a, row >= 4 ? a - 4 * STG_PITCH : (r ? sbase + M_KTAIL + row * 128 + hh * 32 : 0u), l + 1, ct * 4 + hh, row0 + row,
                (16 * r + (row >> 2)) * 64 + rb * 4 + (row & 3));
      if (r == 0 && t < 32)
        *reinterpret_cast<uint4*>(sm + M_KTAIL + t * 16) = lds128(stg + (60 + (t >> 3)) * STG_PITCH + (t & 7) * 16);
    }
  }
  __syncwarp();
  if (lane == 0) mbar_arrive(s_bar + B_EPI + p * 8);
}

constexpr int H_W = 0, H_A = 65536, H_STG = H_A + 131072, H_PITCH = 80, H_TAIL = H_STG + 4 * 64 * H_PITCH, H_BAR = H_TAIL + 512;
__device__ __forceinline__ void helper_mma(float (&acc)[16], const CUtensorMap* m, int row, uint32_t sa, uint32_t sb, uint32_t bar, int wg,
                                           int wu) {
  if (wu == 0 && elect_one()) {
#pragma unroll
    for (int c = 0; c < 4; c++) { mbar_expect(bar + c * 8, 8192); tma_load(sa + c * 8192, m, c * 64, row, bar + c * 8); }
  }
  pin(acc);
#pragma unroll
  for (int c = 0; c < 8; c++) {
    mbar_wait(bar + (c & 3) * 8, c >> 2);
    const uint64_t da = mkdesc(sa + (c & 3) * 8192, 16, 1024, 1), db = mkdesc(sb + c * 8192, 8192, 1024, 1);
    wg_fence();
#pragma unroll
    for (int k = 0; k < 4; k++) wgmma_gemm_n32(acc, da + k * 2, db + k * 128);
    wg_commit();
    if (c >= 1 && c <= 3) {
      wg_wait<1>();
      named_sync(wg + 1, 128);
      if (wu == c - 1 && elect_one()) {
        mbar_expect(bar + (c - 1) * 8, 8192);
        tma_load(sa + (c - 1) * 8192, m, (c + 3) * 64, row, bar + (c - 1) * 8);
      }
    }
    if (c == 3) {
      wg_wait<0>();
      named_sync(wg + 1, 128);
      if (wu == 3 && elect_one()) { mbar_expect(bar + 24, 8192); tma_load(sa + 3 * 8192, m, 7 * 64, row, bar + 24); }
    }
  }
  wg_wait<0>();
  pin(acc);
  named_sync(wg + 1, 128);
}
__device__ __forceinline__ void kv_helper(const MegaParams& P, uint8_t* sm, uint32_t sbase, int wg) {
  const int t = threadIdx.x & 127, lane = t & 31, w4 = t >> 5;
  const int wu = __shfl_sync(0xffffffffu, w4, 0);
  const uint32_t bar_w = sbase + H_BAR, bar = bar_w + 8 + wg * 32;
  if (threadIdx.x == 0) {
    for (int i = 0; i < 17; i++) mbar_init(bar_w + i * 8, 1);
    fence_bar_init();
    mbar_expect(bar_w, 65536);
    for (int c = 0; c < 8; c++) tma_load(sbase + H_W + c * 8192, &P.m[4], 0, c * 64, bar_w);
  }
  const int rb = (blockIdx.x - 128) * 4 + wg;
  const uint32_t sa = sbase + H_A + wg * 32768, stg = sbase + H_STG + wg * 64 * H_PITCH, tail = sbase + H_TAIL + wg * 128;
  float* cs = reinterpret_cast<float*>(sm + H_BAR + 256);
  if (threadIdx.x < 32) cs[lane] = __ldcg(g_colsum + 2048 + lane);
  named_sync(5, 512);
  mbar_wait(bar_w, 0);
  float acc[16];
#pragma unroll 1
  for (int i = 0; i < 10; i++) {
    i = __shfl_sync(0xffffffffu, i, 0);
    const int job = ((i - 2) >> 1 & 1) + ((i - 2) >> 2) * 4, l = job >> 1, r = job & 1, row0 = tok0(r, rb);
    if (i < 2 || !(i & 1)) {
#pragma unroll
      for (int j = 0; j < 16; j++) acc[j] = 0.f;
    }
    if (i >= 2 && wu == 0) {
      if (i & 1) cnt_wait(CNT_O + job * 16 + rb, 128);
      else if (l > 0) cnt_wait(CNT_X + (job - 2) * 16 + rb, 32);
    }
    helper_mma(acc, &P.m[i < 2 ? 5 : ((i & 1) ? 1 : (l ? 0 : 7))], i < 2 ? (wg + 4 * i) * 64 : row0 + ((!(i & 1) && l) ? (l - 1) * S_ : 0), sa,
               sbase + H_W + ((i >= 2 && (i & 1)) ? 64 : 0), bar, wg, wu);
    if (i < 2) {
      const int row = w4 * 16 + (lane & 15);
      const uint32_t a = sbase + H_W + (wg + 4 * i) * 8192 + row * 128;
#pragma unroll
      for (int j = 0; j < 4; j += 2)
        stsm4(a + (((4 + j + (lane >> 4)) ^ (row & 7)) << 4), pack_bf16(acc[4 * j], acc[4 * j + 1]), pack_bf16(acc[4 * j + 2], acc[4 * j + 3]),
              pack_bf16(acc[4 * j + 4], acc[4 * j + 5]), pack_bf16(acc[4 * j + 6], acc[4 * j + 7]));
      fence_async_smem();
      if (i == 1) named_sync(5, 512);
    } else if (i & 1) {
      cnt_wait(CNT_X + job * 16 + rb, 32);
      float mu0, rs0, mu1, rs1;
      row_stats(l + 1, row0 + w4 * 16 + (lane >> 2), mu0, rs0);
      row_stats(l + 1, row0 + w4 * 16 + (lane >> 2) + 8, mu1, rs1);
      const uint32_t saddr = stg + (w4 * 16 + (lane & 15)) * H_PITCH + (lane >> 4) * 16;
      stage_k(acc, 0, saddr, cs + (lane & 3) * 2, mu0, rs0, mu1, rs1);
      emit_v<1>(acc, 2, ((l + 1) & 1) * H_, r, rb, w4 * 16 + (lane >> 2), lane & 3, cs + (lane & 3) * 2, mu0, rs0, mu1, rs1);
      named_sync(wg + 1, 128);
      if (wu < 2) {
        const uint32_t a = stg + t * H_PITCH;
        emit_k<1>(a, t >= 4 ? a - 4 * H_PITCH : (r ? tail + t * 32 : 0u), l + 1, 0, row0 + t, (16 * r + (t >> 2)) * 64 + rb * 4 + (t & 3));
      }
      if (r == 0 && t < 8) *reinterpret_cast<uint4*>(sm + (tail - sbase) + t * 16) = lds128(stg + (60 + (t >> 1)) * H_PITCH + (t & 1) * 16);
      named_sync(wg + 1, 128);
      TM3(12 + job, 4);
      if (wu == 0) cnt_signal(CNT_KV + job * 8);
    }
  }
  named_sync(5, 512);
  if (threadIdx.x < 32) cnt_done();
}

__global__ void __launch_bounds__(640, 1) mega_kernel(const __grid_constant__ MegaParams P) {
  extern __shared__ __align__(1024) uint8_t sm[];
  constexpr uint32_t sbase = 1024;
  if (s2u(sm) != sbase) __trap();
  const uint32_t s_bar = sbase + M_BAR;
  const int tid = threadIdx.x, warp = tid >> 5, lane = tid & 31;
  TM(2, 0);
  if (tid == 0) {
    for (int i = 0; i < 4; i++) {
      mbar_init(s_bar + B_FULL + i * 8, 1); mbar_init(s_bar + B_EMPTY + i * 8, 4);
      mbar_init(s_bar + B_TURN + i * 8, 4); mbar_init(s_bar + B_EPI + i * 8, 4); mbar_init(s_bar + B_FULLR + i * 8, 1);
      mbar_init(s_bar + B_KV + i * 8, 1);
    }
    for (int i = 0; i < 2; i++) { mbar_init(s_bar + B_Q + i * 8, 1); mbar_init(s_bar + B_ODONE + i * 8, 16); }
    mbar_init(s_bar + B_FREE0, 16);
    mbar_init(s_bar + B_RES, 1);
    mbar_init(s_bar + B_PRE, 1);
    mbar_init(s_bar + B_CHK, 1);
    fence_bar_init();
  }
  if (tid < 512) *reinterpret_cast<uint4*>(sm + M_KV + tid * 16) = make_uint4(0x00003f80u, 0u, 0u, 0u);
  fence_async_smem();
  __syncthreads();
  const int wg = __shfl_sync(0xffffffffu, warp >> 2, 0);

  if (wg < 4) {
    asm volatile("setmaxnreg.inc.sync.aligned.u32 112;");
    pdl_wait();
    if (blockIdx.x >= 128) { kv_helper(P, sm, sbase, wg); return; }
    uint32_t pb = PBO ? P.poly_b : POLY_B;
    asm volatile("" : "+r"(pb));
    float s[32], o[12];
    uint32_t p0[16], p1[16];
#pragma unroll
    for (int i = 0; i < 32; i++) s[i] = ((MUFU_MASK >> (i >> 1)) & 1) ? 0.f : EXP_MAGIC;
#pragma unroll
    for (int i = 0; i < 12; i++) o[i] = 0.f;
    uint64_t dq = mkdesc(sbase + M_Q + wg * 2048, 128, 256, 0);
    uint64_t dk0 = mkdesc(sbase + M_KV + k_unit(0, 0) * 8192, 128, 256, 0), dk1 = mkdesc(sbase + M_KV + k_unit(0, 1) * 8192, 128, 256, 0);
    uint64_t dv = mkdesc(sbase + M_KV, 128, 8192, 0);
    uint32_t sched = 0;
#pragma unroll
    for (int lr = 0; lr < 8; lr++) {
      const int pp = (wg - lr) & 3, dly = lr == 6 ? (L6 == 4 ? 3 : L6) : (SCHED >> (4 * (pp + ((lr & 1) ? 8 : (lr & 2) * 2)))) & 3;
      sched |= ((pass_exists(lr, pp) ? dly : 0) | pp << 2) << (4 * lr);
    }
    int pass_code = -1;
    int flush_it = 3;
    int pass_it = -1;
    mbar_wait_long(s_bar + B_Q, 0);
    mbar_wait_long(s_bar + B_KV, 0);
    TM1(3, 3);
    pin(o);
    att_step<false>(s, o, p1, p0, dq, dk0, dv, pb);
    {
#pragma unroll 1
      for (int it = 0; it < 32; it++) {
        const int b = it & 3;
        pin(o);
        att_step<true>(s, o, p0, p1, dq, dk0 + 128, dv, pb);
        att_step<true>(s, o, p1, p0, dq, dk0 + 256, dv + 64, pb);
        att_step<true>(s, o, p0, p1, dq, dk0 + 384, dv + 128, pb);
        att_step<true>(s, o, p1, p0, dq, dk1, dv + 192, pb);
        att_step<true>(s, o, p0, p1, dq, dk1 + 128, dv + 256, pb);
        att_step<true>(s, o, p1, p0, dq, dk1 + 256, dv + 320, pb);
        att_step<true>(s, o, p0, p1, dq, dk1 + 384, dv + 384, pb);
        if (!(WB & 1)) wg_wait<0>();
        const uint64_t dvp = (VV & 32) ? dv + 448 : dv;
        dk0 += 2048; dk1 += 1024; dv += 1024ull << 32;
        if (FL ? it == flush_it : (it == pass_it || b == 3)) {
          const int lr = it >> 2, rnd = lr & 1, layer = lr >> 1, par = layer & 1;
          if ((WB & 3) == 3) wg_wait<0>();
          int t;
          asm volatile("mov.u32 %0, %%tid.x;" : "=r"(t));
          const int ln = t & 31, head = blockIdx.x >> 2;
          const int row0 = (blockIdx.x & 3) * 512 + rnd * 256 + wg * 64;
          pin(p1); pin(o);
          wg_fence();
          pv4(o, p1, dvp + ((VV & 32) ? 0 : 448));
          wg_commit();
          wg_wait<0>();
          pin(o); pin(s);
          if ((it & 7) == 5 && elect_one()) mbar_arrive(s_bar + B_FREE0);
          int code = (VV & 8) ? pass_code : (lr - 1) * 4 + ((wg - lr + 1) & 3);
          if (b == 3) {
            __nv_bfloat16* dst = g_o + (size_t)(row0 + ((t >> 5) & 3) * 16 + (ln >> 2)) * D_ + head * 16 + (ln & 1) * 8 + (ln & 2) * 2;
            const float l0 = __shfl_sync(0xffffffffu, o[0], ln & 28), l1 = __shfl_sync(0xffffffffu, o[2], ln & 28);
            float mx = 0.f;
            if (MX) {
              mx = (fabsf(o[8]) + fabsf(o[9])) + (fabsf(o[10]) + fabsf(o[11])) + ((fabsf(o[4]) + fabsf(o[5])) + (fabsf(o[6]) + fabsf(o[7])));
            } else {
#pragma unroll
              for (int i = 4; i < 12; i++) mx += fabsf(o[i]);
            }
            float i0, i1;
            asm("rcp.approx.ftz.f32 %0, %1;" : "=f"(i0) : "f"(l0));
            asm("rcp.approx.ftz.f32 %0, %1;" : "=f"(i1) : "f"(l1));
            *reinterpret_cast<uint2*>(dst) = make_uint2(pack_bf16(o[4] * i0, o[5] * i0), pack_bf16(o[8] * i0, o[9] * i0));
            *reinterpret_cast<uint2*>(dst + 8 * D_) = make_uint2(pack_bf16(o[6] * i1, o[7] * i1), pack_bf16(o[10] * i1, o[11] * i1));
            mbar_wait(s_bar + B_CHK, par);
            const bool ok = sm[M_CHK + par * 8 + rnd * 4 + wg] && l0 >= 1e-18f && l0 <= 1e37f &&
                            l1 >= 1e-18f && l1 <= 1e37f && mx <= 3e38f;
            uint32_t bad;
            asm volatile("{.reg .pred p, q; setp.eq.u32 p, %1, 0; barrier.red.or.pred.aligned q, %2, 128, p; selp.u32 %0, 1, 0, q;}"
                         : "=r"(bad) : "r"((uint32_t)ok), "r"(wg + 1) : "memory");
            if (bad) {
              att_fallback(P, layer, head, row0, reinterpret_cast<__nv_bfloat16*>(sm + M_Q + rnd * 8192 + wg * 2048), wg + 1);
              fence_async_smem();
              named_sync(wg + 1, 128);
            }
            __syncwarp();
            if (elect_one()) mbar_arrive(s_bar + B_ODONE + rnd * 8);
            if (ODIRECT && (rnd || ODIRECT == 2) && __shfl_sync(0xffffffffu, t & 96, 0) == 0) cnt_signal(CNT_O + lr * 16 + (blockIdx.x & 3) * 4 + wg, 4);
#pragma unroll
            for (int i = 0; i < 32; i++) s[i] = ((MUFU_MASK >> (i >> 1)) & 1) ? TINY : EXP_MAGIC;
#pragma unroll
            for (int i = 0; i < 12; i++) o[i] = TINY;
            if (VV & 8) {
              const int nib = sched & 15;
              sched >>= 4;
              code = nib == 0 ? lr * 4 : (it == pass_it ? pass_code : -1);
              pass_code = lr * 4 + (nib >> 2);
              pass_it = (nib & 3) ? it + (nib & 3) + (L6 == 4 && lr == 6 ? 1 : 0) : -1;
            } else {
              const int nib = (sched >> (4 * lr)) & 15;
              code = nib == 0 ? lr * 4 : (it == pass_it ? code : -1);
              pass_it = (nib & 3) ? it + (nib & 3) + (L6 == 4 && lr == 6 ? 1 : 0) : -1;
            }
            if (VV & 1) dq = mkdesc(sbase + M_Q + 8192, 128, 256, 0) + (uint32_t)(wg * 128 - rnd * 512);
            else dq += rnd ? -512ll : 512ll;
            if (VV & 2) {
              dk0 = mkdesc(sbase + M_KV + k_unit(0, 0) * 8192, 128, 256, 0);
              dk1 = mkdesc(sbase + M_KV + k_unit(0, 1) * 8192, 128, 256, 0);
            } else {
              dk0 -= 4 * 2048; dk1 -= 4 * 1024;
            }
            if (VV & 4) dv = mkdesc(sbase + M_KV, 128, 8192, 0);
            else dv -= 4096ull << 32;
          }
          flush_it = pass_it > it ? pass_it : ((it + 1) | 3);
          if (code >= 0) {
            TM3(24 + code, 4);
            proj_pass(P, sm, sbase, code, wg);
            TM3(24 + code, 5);
          }
          if (it == 31) break;
          if (VV & 16) {
          if (((it + 1) & 4) == 0) {
            if (b == 3) mbar_wait_long(s_bar + B_Q, ((it + 1) >> 3) & 1);
            mbar_wait_long(s_bar + B_KV + ((b + 1) & 3) * 8, ((it + 1) >> 3) & 1);
          } else if (b == 3) {
            mbar_wait_long(s_bar + B_Q + 8, (it >> 3) & 1);
          }
          } else {
            if (b == 3) mbar_wait_long(s_bar + B_Q + (~it & 4) * 2, ((it + 1) >> 3) & 1);
            mbar_wait_long(s_bar + B_KV + ((b + 1) & 3) * 8, ((it + 1) >> 3) & 1);
          }
          pin(o);
          att_step<false>(s, o, p1, p0, dq, dk0, dv, pb);
        } else {
          if (WB & 1) wg_wait<0>();
          if (!(it & 4)) mbar_wait_long(s_bar + B_KV + 8 + b * 8, (it >> 3) & 1);
          att_step<true>(s, o, p1, p0, dq, dk0, dvp + ((VV & 32) ? 0 : 448), pb);
          if (WB & 4) {
            if ((it & 7) == 5) { wg_wait<0>(); if (elect_one()) mbar_arrive(s_bar + B_FREE0); }
            wg_wait<0>();
          } else {
            wg_wait<0>();
            if ((it & 7) == 5 && elect_one()) mbar_arrive(s_bar + B_FREE0);
          }
        }
      }
    }
  } else {
    asm volatile("setmaxnreg.dec.sync.aligned.u32 32;");
    if (blockIdx.x >= 128) return;
    const int w4 = __shfl_sync(0xffffffffu, warp & 3, 0);
    const int rb = blockIdx.x >> 3, ct = blockIdx.x & 7;
    if (w4 == 0) {
      int code = 0, npass = 1;
      bool gated = true;
#pragma unroll 1
      while (code < 32) {
        code = __shfl_sync(0xffffffffu, code, 0);
        const int job = code >> 2, p = code & 3;
        const CUtensorMap* mb = b_map(P, code);
        const CUtensorMap* ma = &P.m[p == 0 ? 1 : 0];
        const int colb = b_col(code), rowa = tok0(job & 1, rb) + (p == 0 ? 0 : (code >> 3) * S_);
#pragma unroll
        for (int c = 0; c < 4; c++) {
          if (code > 0) mbar_wait(s_bar + B_EMPTY + c * 8, npass);
          if (code > 0 && c == 0) TM2(24 + prev_pass(code), 2);
          if (code > 0 && c == 3) TM2(24 + prev_pass(code), 3);
          if (elect_one()) {
            if (job & 1) {
              const uint32_t bar = s_bar + B_FULLR + c * 8;
              mbar_expect(bar, gated ? 32768 : 16384);
              tma_load(sbase + M_STAGE + c * 16384, mb, colb, c * 128, bar);
              tma_load(sbase + M_STAGE + c * 16384 + 8192, mb, colb, c * 128 + 64, bar);
            } else {
              issue_b(sbase, mb, colb, c, c);
              if (!gated) issue_a(sbase, ma, rowa, c, c);
            }
          }
        }
        if (gated) {
          if (p == 0) {
            if (code == 0) pdl_wait();
            mbar_wait_long(s_bar + B_ODONE + (job & 1) * 8, (job >> 1) & 1);
            cnt_wait(CNT_O + job * 16 + rb, 128);
            TM2(12 + job, 1);
          } else {
            mbar_wait_long(s_bar + B_EPI, job & 1);
            cnt_wait(CNT_X + job * 16 + rb, 32);
            TM2(12 + job, 3);
          }
          if (elect_one()) {
            if (job & 1) {
#pragma unroll
              for (int c = 0; c < 8; c++) tma_load(sbase + M_KV + res_unit(c) * 8192, ma, c * 64, rowa, s_bar + B_FULLR + (c >> 1) * 8);
            } else {
#pragma unroll
              for (int c = 0; c < 4; c++) issue_a(sbase, ma, rowa, c, c);
            }
          }
          if (p == 0) {
            if (code > 0) { const int prev = prev_pass(code); mbar_wait_long(s_bar + B_EPI + (prev & 3) * 8, (prev >> 2) & 1); }
            if (elect_one()) {
              if (FP) { fence_async_smem(); asm volatile("fence.proxy.async.global;" ::: "memory"); }
              else asm volatile("fence.proxy.async;" ::: "memory");
              mbar_expect(s_bar + B_RES, 8192);
              tma_load(sbase + M_STG, &P.m[job < 2 ? 7 : 0], ct * 64, tok0(job & 1, rb) + (job < 2 ? 0 : ((job >> 1) - 1) * S_), s_bar + B_RES);
            }
          }
        }
        TM2(24 + code, 0);
        npass ^= 1;
        code = next_pass(code);
        gated = p == 0 || (code & 3) == 0;
      }
    } else if (w4 == 1) {
#pragma unroll 1
      for (int job = 0; job < 8; job++) {
        mbar_wait_long(s_bar + B_ODONE + (job & 1) * 8, (job >> 1) & 1);
        TM2(3 + job, 0);
        if (!ODIRECT || (ODIRECT == 1 && !(job & 1))) {
          asm volatile("fence.acq_rel.gpu;" ::: "memory");
          if (lane < 4) asm volatile("red.relaxed.gpu.global.add.u32 [%0], 4;" ::"l"(g_cnt + (CNT_O + job * 16 + (blockIdx.x & 3) * 4 + lane) * CNT_STRIDE) : "memory");
        }
        TM2(12 + job, 0);
        if (job >= 6) continue;
        mbar_wait_long(s_bar + B_EPI, job & 1);
        TM2(12 + job, 2);
        if (!XDIRECT || (XDIRECT == 1 && !(job & 1))) cnt_signal(CNT_X + job * 16 + rb, 4);
        if (pass_exists(job, 1)) {
          mbar_wait_long(s_bar + B_EPI + 8, job & 1);
          mbar_wait_long(s_bar + B_EPI + 16, job & 1);
          TM2(12 + job, 4);
          cnt_signal(CNT_KV + job * 8 + ct);
        }
        mbar_wait_long(s_bar + B_EPI + 24, job & 1);
        TM2(12 + job, 5);
        cnt_signal(CNT_Q + (job * 4 + (rb >> 2)) * 8 + ct);
      }
    } else if (w4 == 2) {
      pdl_wait();
      load_q(sbase, 0, 0); load_kv(sbase, 0, 0);
      mbar_wait(s_bar + B_KV + 8, 0);
      load_kv(sbase, 0, 1); load_q(sbase, 0, 1);
#pragma unroll 1
      for (int job = 0; job < 6; job++) {
        const int l = job >> 1, r = job & 1;
        mbar_wait_long(s_bar + B_ODONE + r * 8, l & 1);
        if (r == 0) mbar_wait_long(s_bar + B_FREE0, l & 1);
        mbar_wait_long(s_bar + B_TURN + r * 24, job & 1);
        cnt_wait(CNT_KV + job * 8 + ((l & 1) ? blockIdx.x >> 4 : 0), 16);
        TM2(3 + job, 1);
        load_kv(sbase, l + 1, r);
        cnt_wait(CNT_Q + (job * 4 + (blockIdx.x & 3)) * 8 + (blockIdx.x >> 4), 4);
        TM2(3 + job, 2);
        load_q(sbase, l + 1, r);
      }
    } else {
      pdl_wait();
#pragma unroll 1
      for (int job = -1; job < 6; job++) {
        if (job & 1) {
          const int l = (job + 1) >> 1, head = blockIdx.x >> 2;
          if (job > 0) { mbar_wait_long(s_bar + B_KV + 24, l & 1); mbar_wait_long(s_bar + B_Q + 8, l & 1); }
          const float* nk = g_nk + (l * H_ + ((l & 1) ? 0 : head)) * 64;
          unsigned qn = __float_as_uint(__ldcg(g_nq + (l * 8 + (head >> 2)) * 128 + (blockIdx.x & 3) * 32 + lane));
          const unsigned kn = __reduce_max_sync(0xffffffffu, max(__float_as_uint(__ldcg(nk + lane)), __float_as_uint(__ldcg(nk + 32 + lane))));
          qn = max(qn, __shfl_xor_sync(0xffffffffu, qn, 1));
          qn = max(qn, __shfl_xor_sync(0xffffffffu, qn, 2));
          if (!(lane & 3)) sm[M_CHK + (l & 1) * 8 + (lane >> 2)] = __uint_as_float(qn) * __uint_as_float(kn) <= SCORE_LIMIT * SCORE_LIMIT;
          __syncwarp();
          if (elect_one()) mbar_arrive(s_bar + B_CHK);
        }
        if (job == 5) break;
        job++;
        float c[6];
#pragma unroll
        for (int i = 0; i < 6; i++) {
          const int p = 1 + (i >> 1);
          c[i] = __ldcg(g_colsum + ((job & 2) ? (p == 3 ? 0 : p * 512) : 1536) + ct * 64 + (i & 1) * 32 + lane);
        }
        mbar_wait_long(s_bar + B_TURN, job & 1);
#pragma unroll
        for (int i = 0; i < 6; i++) reinterpret_cast<float*>(sm + M_CS)[i * 32 + lane] = c[i];
        __syncwarp();
        if (elect_one()) mbar_arrive(s_bar + B_PRE);
        job--;
      }
    }
    named_sync(5, 128);
    if (w4 == 0) cnt_done();
  }
}

typedef CUresult (*EncodeFn)(CUtensorMap*, CUtensorMapDataType, cuuint32_t, void*, const cuuint64_t*, const cuuint64_t*,
                             const cuuint32_t*, const cuuint32_t*, CUtensorMapInterleave, CUtensorMapSwizzle,
                             CUtensorMapL2promotion, CUtensorMapFloatOOBfill);

void make_map(EncodeFn enc, CUtensorMap* m, const void* p, int rows, int cols) {
  cuuint64_t dim[2] = {(cuuint64_t)cols, (cuuint64_t)rows};
  cuuint64_t str[1] = {(cuuint64_t)cols * 2};
  cuuint32_t box[2] = {64, 64};
  cuuint32_t es[2] = {1, 1};
  enc(m, CU_TENSOR_MAP_DATA_TYPE_BFLOAT16, 2, const_cast<void*>(p), dim, str, box, es, CU_TENSOR_MAP_INTERLEAVE_NONE,
      CU_TENSOR_MAP_SWIZZLE_128B, CU_TENSOR_MAP_L2_PROMOTION_L2_128B, CU_TENSOR_MAP_FLOAT_OOB_FILL_NONE);
}

template <typename... KA, typename... A>
void launch(void (*k)(KA...), int grid, int block, int smem, bool pdl, A... args) {
  cudaLaunchConfig_t cfg = {};
  cfg.gridDim = dim3(grid); cfg.blockDim = dim3(block); cfg.dynamicSmemBytes = smem; cfg.stream = cudaStreamPerThread;
  cudaLaunchAttribute at[2];
  at[0].id = cudaLaunchAttributePreferredSharedMemoryCarveout;
  at[0].val.sharedMemCarveout = 100;
  at[1].id = cudaLaunchAttributeProgrammaticStreamSerialization;
  at[1].val.programmaticStreamSerializationAllowed = 1;
  cfg.attrs = at; cfg.numAttrs = pdl ? 2 : 1;
  cudaLaunchKernelEx(&cfg, k, KA(args)...);
}

struct HostState {
  bool init;
  const void* in[8];
  MegaParams mp;
};
HostState hs;

}

extern "C" void kernel_launch(void* const* d_in, const int* in_sizes, int n_in, void* d_out, int out_size) {
  const __nv_bfloat16* A_x = (const __nv_bfloat16*)d_in[0];
  const __nv_bfloat16* A_wqkv = (const __nv_bfloat16*)d_in[1];
  const __nv_bfloat16* A_wo = (const __nv_bfloat16*)d_in[2];
  const __nv_bfloat16* B_wq = (const __nv_bfloat16*)d_in[4];
  const __nv_bfloat16* B_wk = (const __nv_bfloat16*)d_in[5];
  const __nv_bfloat16* B_wv = (const __nv_bfloat16*)d_in[6];
  const __nv_bfloat16* B_wo = (const __nv_bfloat16*)d_in[7];
  bool same = hs.init;
  for (int i = 0; i < 8; i++) same = same && hs.in[i] == d_in[i];
  if (!same) {
    void* fn = nullptr;
    cudaDriverEntryPointQueryResult qr;
    cudaGetDriverEntryPoint("cuTensorMapEncodeTiled", &fn, cudaEnableDefault, &qr);
    EncodeFn enc = (EncodeFn)fn;
    void *px, *po, *pw;
    cudaGetSymbolAddress(&px, g_x);
    cudaGetSymbolAddress(&po, g_o);
    cudaGetSymbolAddress(&pw, g_wkv);
    make_map(enc, &hs.mp.m[7], A_x, S_, D_);
    make_map(enc, &hs.mp.m[0], px, 3 * S_, D_);
    make_map(enc, &hs.mp.m[1], po, S_, D_);
    make_map(enc, &hs.mp.m[2], A_wqkv, D_, 1536);
    make_map(enc, &hs.mp.m[3], B_wq, D_, 512);
    make_map(enc, &hs.mp.m[4], pw, D_, 32);
    make_map(enc, &hs.mp.m[5], A_wo, D_, D_);
    make_map(enc, &hs.mp.m[6], B_wo, D_, D_);
    hs.mp.poly_b = POLY_B;
    hs.mp.x0 = A_x; hs.mp.wqkv = A_wqkv; hs.mp.wq = B_wq; hs.mp.wk = B_wk;
    cudaFuncSetAttribute(prep_kernel, cudaFuncAttributePreferredSharedMemoryCarveout, 100);
    cudaFuncSetAttribute(g1a_kernel, cudaFuncAttributeMaxDynamicSharedMemorySize, G1A_SMEM);
    cudaFuncSetAttribute(mega_kernel, cudaFuncAttributeMaxDynamicSharedMemorySize, MEGA_SMEM);
    for (int i = 0; i < 8; i++) hs.in[i] = d_in[i];
    hs.init = true;
  }
  hs.mp.out = (__nv_bfloat16*)d_out;
  launch(prep_kernel, 130, 256, 0, false, A_x, A_wqkv, B_wq, B_wk, B_wv, A_wo, B_wo);
  launch(g1a_kernel, 128, 288, G1A_SMEM, true, hs.mp.m[7], hs.mp.m[2]);
  launch(mega_kernel, 132, 640, MEGA_SMEM, true, hs.mp);
}
```
